```python
import torch

def _softmax(x, axis=-1):
    return torch.softmax(x, dim=axis)
def _gelu(x):
    return torch.nn.functional.gelu(x, approximate="tanh")
def _silu(x):
    return torch.nn.functional.silu(x)
def _sigmoid(x):
    return torch.sigmoid(x)
def _layernorm(x, axis=-1, eps=1e-5):
    m = x.mean(dim=axis, keepdim=True)
    v = x.var(dim=axis, keepdim=True, unbiased=False)
    return (x - m) / torch.sqrt(v + eps)
def _scatter_add(tgt, idx, src, axis=0):
    return tgt.clone().index_add_(axis, idx, src)
def _segment_sum(src, seg, n):
    out = torch.zeros((n,) + src.shape[1:], dtype=src.dtype)
    return out.index_add_(0, seg, src)
def _pad(x, pw):
    flat = tuple(v for pair in reversed(pw) for v in pair)
    return torch.nn.functional.pad(x, flat)

kernel_name = 'gated_mix__ssm_conv_s4__ssm_conv_s4d__prompt'

def setup_inputs():

    _w = (lambda a: (lambda t: t.to(torch.bfloat16) if t.is_floating_point() else t)(torch.as_tensor(a)))
    def _A_setup():
        B, L, D, N = 1, 2048, 512, 128
        A_re = -(lambda _x: torch.exp(torch.as_tensor(_x)))((lambda *s: torch.randn(*s, dtype=torch.bfloat16) * 6.4)(D, N))
        A_im = torch.pi * (lambda *s: torch.randn(*s, dtype=torch.bfloat16) * 0.05)(D, N)
        B_re = (lambda *s: torch.randn(*s, dtype=torch.bfloat16) * 0.1)(D, N)
        B_im = (lambda *s: torch.randn(*s, dtype=torch.bfloat16) * 0.1)(D, N)
        C_re = (lambda *s: torch.randn(*s, dtype=torch.bfloat16) * 0.1)(D, N)
        C_im = (lambda *s: torch.randn(*s, dtype=torch.bfloat16) * 0.1)(D, N)
        log_dt = (lambda *s: torch.randn(*s, dtype=torch.bfloat16) * 0.05)(D) * 0.5 - 4.0
        Dskip = (lambda *s: torch.randn(*s, dtype=torch.bfloat16) * 0.05)(D)
        return {
            "u": _w((lambda *s: torch.randn(*s, dtype=torch.bfloat16) * 0.05)(B, L, D)),
            "A_re": _w(A_re),
            "A_im": _w(A_im),
            "B_re": _w(B_re),
            "B_im": _w(B_im),
            "C_re": _w(C_re),
            "C_im": _w(C_im),
            "log_dt": _w(log_dt),
            "Dskip": _w(Dskip),
        }
    _A_in = _A_setup()

    def _B_setup():
        Bsz, L, D, N = 1, 2048, 512, 128
        return {
            "u": _w((lambda *s: torch.randn(*s, dtype=torch.bfloat16) * 0.05)(Bsz, L, D)),
            "log_A_real": _w((lambda *s: torch.randn(*s, dtype=torch.bfloat16) * 6.4)(D, N) * 0.5),
            "A_imag": _w((lambda *s: torch.randn(*s, dtype=torch.bfloat16) * 0.05)(D, N) * 3.14),
            "C_real": _w((lambda *s: torch.randn(*s, dtype=torch.bfloat16) * 0.05)(D, N) / N ** 0.5),
            "C_imag": _w((lambda *s: torch.randn(*s, dtype=torch.bfloat16) * 0.05)(D, N) / N ** 0.5),
            "log_dt": _w((lambda *s: torch.randn(*s, dtype=torch.bfloat16) * 0.05)(D) * 0.5 - 4.0),
            "D_skip": _w((lambda *s: torch.randn(*s, dtype=torch.bfloat16) * 0.05)(D)),
        }
    _B_in = _B_setup()

    return {
        "A_u": _A_in["u"],
        "A_A_re": _A_in["A_re"],
        "A_A_im": _A_in["A_im"],
        "A_B_re": _A_in["B_re"],
        "A_B_im": _A_in["B_im"],
        "A_C_re": _A_in["C_re"],
        "A_C_im": _A_in["C_im"],
        "A_log_dt": _A_in["log_dt"],
        "A_Dskip": _A_in["Dskip"],
        "B_u": _B_in["u"],
        "B_log_A_real": _B_in["log_A_real"],
        "B_A_imag": _B_in["A_imag"],
        "B_C_real": _B_in["C_real"],
        "B_C_imag": _B_in["C_imag"],
        "B_log_dt": _B_in["log_dt"],
        "B_D_skip": _B_in["D_skip"],
        "gate_w": _w((lambda *s: torch.randn(*s, dtype=torch.bfloat16) * 0.05)(512) * 16.0),
    }

def reference(A_u, A_A_re, A_A_im, A_B_re, A_B_im, A_C_re, A_C_im, A_log_dt, A_Dskip, B_u, B_log_A_real, B_A_imag, B_C_real, B_C_imag, B_log_dt, B_D_skip, gate_w):
    def _A_ref(u, A_re, A_im, B_re, B_im, C_re, C_im, log_dt, Dskip):
        Bsz, L, D = u.shape
        dt = torch.exp(log_dt)[:, None]
        A = A_re + 1j * A_im
        Bc = B_re + 1j * B_im
        Cc = C_re + 1j * C_im
        logdA = dt * A
        dB = dt * Bc
        l = (lambda x, dt: x.to(dt))(torch.arange(L), A_re.dtype)
        P = torch.exp(logdA[:, :, None] * l[None, None, :])
        K = torch.einsum("dn,dnl,dn->dl", Cc, P, dB).real
        L2 = 2 * L
        Kp = _pad(K, ((0, 0), (0, L)))
        up = (lambda x, *d: x.permute(*d))(u, 0, 2, 1)
        up = _pad(up, ((0, 0), (0, 0), (0, L)))
        Kf = (lambda x, axes=(-2,-1): torch.fft.rfft2(x.float(), dim=axes))(Kp[:, None, :], axes=(-2, -1))
        Uf = (lambda x, axes=(-2,-1): torch.fft.rfft2(x.float(), dim=axes))(up[:, :, None, :], axes=(-2, -1))
        Yf = Uf * Kf[None, :, :, :]
        y = (lambda x, s, axes=(-2,-1): torch.fft.irfft2(x, s=s, dim=axes).to(torch.bfloat16))(Yf, (1, L2), axes=(-2, -1))[:, :, 0, :L]
        y = (lambda x, *d: x.permute(*d))(y, 0, 2, 1) + u * Dskip[None, None, :]
        return y

    def _B_ref(u, log_A_real, A_imag, C_real, C_imag, log_dt, D_skip):
        L = u.shape[1]
        dt = torch.exp(log_dt)
        A = -torch.exp(log_A_real) + 1j * A_imag
        C = (C_real + 1j * C_imag) * dt[:, None]
        pos = (lambda x, dt: x.to(dt))(torch.arange(L), log_dt.dtype)
        P = torch.exp((A * dt[:, None])[:, :, None] * pos[None, None, :])
        K = 2.0 * torch.einsum("dn,dnl->dl", C, P).real
        L2 = 2 * L
        u_t = (lambda x, *d: x.permute(*d))(u, 0, 2, 1)
        Kf = (lambda x, *a, **k: torch.fft.rfft(x.float(), *a, **k))(K, L2)
        Uf = (lambda x, *a, **k: torch.fft.rfft(x.float(), *a, **k))(u_t, L2)
        y = (lambda x, *a, **k: torch.fft.irfft(x, *a, **k).to(torch.bfloat16))(Uf * Kf[None, :, :], L2)[:, :, :L]
        y = (lambda x, *d: x.permute(*d))(y, 0, 2, 1)
        return y + u * D_skip[None, None, :]

    x = A_u
    g = _sigmoid((x * gate_w).sum(-1, keepdims=True))
    a = _A_ref(x, A_A_re, A_A_im, A_B_re, A_B_im, A_C_re, A_C_im, A_log_dt, A_Dskip)
    b = _B_ref(x, B_log_A_real, B_A_imag, B_C_real, B_C_imag, B_log_dt, B_D_skip)
    return g * a + (1 - g) * b
```

```cpp
#include <cuda_runtime.h>
#include <cuda_bf16.h>
#include <cuda_fp16.h>
#include <cuda.h>
#include <stdint.h>

namespace {

constexpr int SEQ = 2048, DIM = 512, NMODE = 128;
constexpr int NCTA = 128, NTHR = 512;

constexpr int SM_RAW  = 0;
constexpr int UA_ARR  = 72 * 16;
constexpr int UA_CH   = 4 * UA_ARR;
constexpr int SM_UA   = 32768;
constexpr int F5_OFF = 0, F3_OFF = 3104, F9_OFF = 6208, F7_OFF = 8256, FS_CH = 10304;
constexpr int SM_FS   = SM_UA + 4 * UA_CH;
constexpr int TW_W = 0, TW_X = 592, TW_5 = 688, TW_3 = 752, TW_9 = 816, TW_7 = 900, TW_TOT = 984;
constexpr int TAB_SZ  = TW_TOT * 4;
constexpr int SM_TAB  = SM_FS + 4 * FS_CH;
constexpr int SM_CST  = SM_TAB + 8 * TAB_SZ;
constexpr int PART_SZ = 644 * 4;
constexpr int SM_PART = SM_CST + 8 * 1536;
constexpr int SM_GW   = SM_PART + 16 * PART_SZ;
constexpr int SM_BAR  = SM_GW + 2 * 32 * 40 * 4;
constexpr int SM_DUMMY = SM_BAR + 64;
constexpr int SM_TOTAL = SM_DUMMY + 64;

__device__ uint32_t g_gate[SEQ];
__device__ unsigned int g_counter;

struct Params {
  const __nv_bfloat16* u;
  const __nv_bfloat16* pm[2][6];
  const __nv_bfloat16* logdt[2];
  const __nv_bfloat16* dskip[2];
  const __nv_bfloat16* gate_w;
  __nv_bfloat16* out;
};

__device__ __forceinline__ void wgmma_n32(float* d, uint32_t a0, uint32_t a1, uint32_t a2, uint32_t a3, uint64_t desc) {
  asm volatile("wgmma.mma_async.sync.aligned.m64n32k16.f32.bf16.bf16 {%0, %1, %2, %3, %4, %5, %6, %7, %8, %9, %10, %11, %12, %13, %14, %15}, {%16, %17, %18, %19}, %20, 1, 1, 1, 0;\n"
    : "+f"(d[0]), "+f"(d[1]), "+f"(d[2]), "+f"(d[3]), "+f"(d[4]), "+f"(d[5]), "+f"(d[6]), "+f"(d[7]), "+f"(d[8]), "+f"(d[9]), "+f"(d[10]), "+f"(d[11]), "+f"(d[12]), "+f"(d[13]), "+f"(d[14]), "+f"(d[15])
    : "r"(a0), "r"(a1), "r"(a2), "r"(a3), "l"(desc));
}

__device__ __forceinline__ void wgmma_n40(float* d, uint32_t a0, uint32_t a1, uint32_t a2, uint32_t a3, uint64_t desc) {
  asm volatile("wgmma.mma_async.sync.aligned.m64n40k16.f32.bf16.bf16 {%0, %1, %2, %3, %4, %5, %6, %7, %8, %9, %10, %11, %12, %13, %14, %15, %16, %17, %18, %19}, {%20, %21, %22, %23}, %24, 1, 1, 1, 0;\n"
    : "+f"(d[0]), "+f"(d[1]), "+f"(d[2]), "+f"(d[3]), "+f"(d[4]), "+f"(d[5]), "+f"(d[6]), "+f"(d[7]), "+f"(d[8]), "+f"(d[9]), "+f"(d[10]), "+f"(d[11]), "+f"(d[12]), "+f"(d[13]), "+f"(d[14]), "+f"(d[15]), "+f"(d[16]), "+f"(d[17]), "+f"(d[18]), "+f"(d[19])
    : "r"(a0), "r"(a1), "r"(a2), "r"(a3), "l"(desc));
}

__device__ __forceinline__ void wgmma_n48(float* d, uint32_t a0, uint32_t a1, uint32_t a2, uint32_t a3, uint64_t desc) {
  asm volatile("wgmma.mma_async.sync.aligned.m64n48k16.f32.bf16.bf16 {%0, %1, %2, %3, %4, %5, %6, %7, %8, %9, %10, %11, %12, %13, %14, %15, %16, %17, %18, %19, %20, %21, %22, %23}, {%24, %25, %26, %27}, %28, 1, 1, 1, 0;\n"
    : "+f"(d[0]), "+f"(d[1]), "+f"(d[2]), "+f"(d[3]), "+f"(d[4]), "+f"(d[5]), "+f"(d[6]), "+f"(d[7]), "+f"(d[8]), "+f"(d[9]), "+f"(d[10]), "+f"(d[11]), "+f"(d[12]), "+f"(d[13]), "+f"(d[14]), "+f"(d[15]), "+f"(d[16]), "+f"(d[17]), "+f"(d[18]), "+f"(d[19]), "+f"(d[20]), "+f"(d[21]), "+f"(d[22]), "+f"(d[23])
    : "r"(a0), "r"(a1), "r"(a2), "r"(a3), "l"(desc));
}

__device__ __forceinline__ void wgmma_n56(float* d, uint32_t a0, uint32_t a1, uint32_t a2, uint32_t a3, uint64_t desc) {
  asm volatile("wgmma.mma_async.sync.aligned.m64n56k16.f32.bf16.bf16 {%0, %1, %2, %3, %4, %5, %6, %7, %8, %9, %10, %11, %12, %13, %14, %15, %16, %17, %18, %19, %20, %21, %22, %23, %24, %25, %26, %27}, {%28, %29, %30, %31}, %32, 1, 1, 1, 0;\n"
    : "+f"(d[0]), "+f"(d[1]), "+f"(d[2]), "+f"(d[3]), "+f"(d[4]), "+f"(d[5]), "+f"(d[6]), "+f"(d[7]), "+f"(d[8]), "+f"(d[9]), "+f"(d[10]), "+f"(d[11]), "+f"(d[12]), "+f"(d[13]), "+f"(d[14]), "+f"(d[15]), "+f"(d[16]), "+f"(d[17]), "+f"(d[18]), "+f"(d[19]), "+f"(d[20]), "+f"(d[21]), "+f"(d[22]), "+f"(d[23]), "+f"(d[24]), "+f"(d[25]), "+f"(d[26]), "+f"(d[27])
    : "r"(a0), "r"(a1), "r"(a2), "r"(a3), "l"(desc));
}

__device__ __forceinline__ void wgmma_n64(float* d, uint32_t a0, uint32_t a1, uint32_t a2, uint32_t a3, uint64_t desc) {
  asm volatile("wgmma.mma_async.sync.aligned.m64n64k16.f32.bf16.bf16 {%0, %1, %2, %3, %4, %5, %6, %7, %8, %9, %10, %11, %12, %13, %14, %15, %16, %17, %18, %19, %20, %21, %22, %23, %24, %25, %26, %27, %28, %29, %30, %31}, {%32, %33, %34, %35}, %36, 1, 1, 1, 0;\n"
    : "+f"(d[0]), "+f"(d[1]), "+f"(d[2]), "+f"(d[3]), "+f"(d[4]), "+f"(d[5]), "+f"(d[6]), "+f"(d[7]), "+f"(d[8]), "+f"(d[9]), "+f"(d[10]), "+f"(d[11]), "+f"(d[12]), "+f"(d[13]), "+f"(d[14]), "+f"(d[15]), "+f"(d[16]), "+f"(d[17]), "+f"(d[18]), "+f"(d[19]), "+f"(d[20]), "+f"(d[21]), "+f"(d[22]), "+f"(d[23]), "+f"(d[24]), "+f"(d[25]), "+f"(d[26]), "+f"(d[27]), "+f"(d[28]), "+f"(d[29]), "+f"(d[30]), "+f"(d[31])
    : "r"(a0), "r"(a1), "r"(a2), "r"(a3), "l"(desc));
}


__device__ __forceinline__ uint32_t smem_u32(const void* p) { return (uint32_t)__cvta_generic_to_shared(p); }
__device__ __forceinline__ uint64_t mkdesc(uint32_t addr, uint32_t lbo, uint32_t sbo) {
  return (uint64_t)((addr & 0x3FFFF) >> 4) | ((uint64_t)(lbo >> 4) << 16) | ((uint64_t)(sbo >> 4) << 32);
}
__device__ __forceinline__ uint32_t lds32(uint32_t a) { uint32_t v; asm volatile("ld.shared.u32 %0, [%1];" : "=r"(v) : "r"(a) : "memory"); return v; }
__device__ __forceinline__ float lds32f(uint32_t a) { float v; asm volatile("ld.shared.f32 %0, [%1];" : "=f"(v) : "r"(a) : "memory"); return v; }
__device__ __forceinline__ uint4 lds128(uint32_t a) { uint4 v; asm volatile("ld.shared.v4.u32 {%0,%1,%2,%3}, [%4];" : "=r"(v.x), "=r"(v.y), "=r"(v.z), "=r"(v.w) : "r"(a) : "memory"); return v; }
__device__ __forceinline__ void sts16(uint32_t a, uint16_t v) { asm volatile("st.shared.u16 [%0], %1;" :: "r"(a), "h"(v) : "memory"); }
__device__ __forceinline__ void sts32(uint32_t a, uint32_t v) { asm volatile("st.shared.u32 [%0], %1;" :: "r"(a), "r"(v) : "memory"); }
__device__ __forceinline__ void sts64f(uint32_t a, float x, float y) { asm volatile("st.shared.v2.f32 [%0], {%1,%2};" :: "r"(a), "f"(x), "f"(y) : "memory"); }
__device__ __forceinline__ void sts128(uint32_t a, uint32_t x, uint32_t y, uint32_t z, uint32_t w) { asm volatile("st.shared.v4.u32 [%0], {%1,%2,%3,%4};" :: "r"(a), "r"(x), "r"(y), "r"(z), "r"(w) : "memory"); }
__device__ __forceinline__ void ldsm4t(uint32_t a, uint32_t& r0, uint32_t& r1, uint32_t& r2, uint32_t& r3) {
  asm volatile("ldmatrix.sync.aligned.m8n8.x4.trans.shared.b16 {%0,%1,%2,%3}, [%4];" : "=r"(r0), "=r"(r1), "=r"(r2), "=r"(r3) : "r"(a) : "memory");
}
__device__ __forceinline__ void stsm4(uint32_t a, uint32_t r0, uint32_t r1, uint32_t r2, uint32_t r3) {
  asm volatile("stmatrix.sync.aligned.m8n8.x4.shared.b16 [%0], {%1,%2,%3,%4};" :: "r"(a), "r"(r0), "r"(r1), "r"(r2), "r"(r3) : "memory");
}
__device__ __forceinline__ void stsm4t(uint32_t a, uint32_t r0, uint32_t r1, uint32_t r2, uint32_t r3) {
  asm volatile("stmatrix.sync.aligned.m8n8.x4.trans.shared.b16 [%0], {%1,%2,%3,%4};" :: "r"(a), "r"(r0), "r"(r1), "r"(r2), "r"(r3) : "memory");
}
__device__ __forceinline__ void mma_bf16(float* c, uint32_t a0, uint32_t a1, uint32_t a2, uint32_t a3, uint32_t b0, uint32_t b1) {
  asm volatile("mma.sync.aligned.m16n8k16.row.col.f32.bf16.bf16.f32 {%0,%1,%2,%3}, {%4,%5,%6,%7}, {%8,%9}, {%0,%1,%2,%3};"
    : "+f"(c[0]), "+f"(c[1]), "+f"(c[2]), "+f"(c[3]) : "r"(a0), "r"(a1), "r"(a2), "r"(a3), "r"(b0), "r"(b1));
}
__device__ __forceinline__ void mma_f16(float* c, uint32_t a0, uint32_t a1, uint32_t a2, uint32_t a3, uint32_t b0, uint32_t b1) {
  asm volatile("mma.sync.aligned.m16n8k16.row.col.f32.f16.f16.f32 {%0,%1,%2,%3}, {%4,%5,%6,%7}, {%8,%9}, {%0,%1,%2,%3};"
    : "+f"(c[0]), "+f"(c[1]), "+f"(c[2]), "+f"(c[3]) : "r"(a0), "r"(a1), "r"(a2), "r"(a3), "r"(b0), "r"(b1));
}
__device__ __forceinline__ void bar_sync(int id, int n) { asm volatile("bar.sync %0, %1;" :: "r"(id), "r"(n) : "memory"); }
__device__ __forceinline__ void bar_arrive(int id, int n) { asm volatile("bar.arrive %0, %1;" :: "r"(id), "r"(n) : "memory"); }
__device__ __forceinline__ float ex2f(float x) { float y; asm("ex2.approx.ftz.f32 %0, %1;" : "=f"(y) : "f"(x)); return y; }
__device__ __forceinline__ float sinaf(float x) { float y; asm("sin.approx.ftz.f32 %0, %1;" : "=f"(y) : "f"(x)); return y; }
__device__ __forceinline__ float cosaf(float x) { float y; asm("cos.approx.ftz.f32 %0, %1;" : "=f"(y) : "f"(x)); return y; }
__device__ __forceinline__ uint32_t pack_h2(float lo, float hi) { uint32_t r; asm("cvt.rn.f16x2.f32 %0, %1, %2;" : "=r"(r) : "f"(hi), "f"(lo)); return r; }
__device__ __forceinline__ uint32_t pack_bf2(float lo, float hi) { uint32_t r; asm("cvt.rn.bf16x2.f32 %0, %1, %2;" : "=r"(r) : "f"(hi), "f"(lo)); return r; }
__device__ __forceinline__ float bf_lo(uint32_t v) { return __uint_as_float(v << 16); }
__device__ __forceinline__ float bf_hi(uint32_t v) { return __uint_as_float(v & 0xffff0000u); }
__device__ __forceinline__ float bf16_round(float x) { return __bfloat162float(__float2bfloat16_rn(x)); }
__device__ __forceinline__ float ldbf(const __nv_bfloat16* p) { return __uint_as_float((uint32_t)__ldg((const unsigned short*)p) << 16); }

struct cf { float x, y; };
__device__ __forceinline__ cf cmul(cf a, cf b) { cf r; r.x = a.x * b.x - a.y * b.y; r.y = a.x * b.y + a.y * b.x; return r; }
__device__ __forceinline__ cf csq(cf a) { cf r; r.x = a.x * a.x - a.y * a.y; r.y = (a.x + a.x) * a.y; return r; }
__device__ __forceinline__ cf cexp_fast(float a2, float th, float x) {
  float e = ex2f(a2 * x), ph = th * x; cf r; r.x = e * cosaf(ph); r.y = e * sinaf(ph); return r;
}
__device__ __forceinline__ uint32_t pack_conj(cf a) { return pack_h2(a.x, -a.y); }
__device__ __forceinline__ uint32_t hcmul(uint32_t B1, uint32_t B2, uint32_t C) {
  __half2 b1 = *reinterpret_cast<__half2*>(&B1), b2 = *reinterpret_cast<__half2*>(&B2), c = *reinterpret_cast<__half2*>(&C);
  __half2 r = __hfma2(b2, __high2half2(c), __hmul2(b1, __low2half2(c)));
  return *reinterpret_cast<uint32_t*>(&r);
}

__device__ __forceinline__ void kgen_mode(uint32_t cst, uint32_t sel, float gf, uint32_t& q0, uint32_t& q1, uint32_t* av) {
  uint4 c0 = lds128(cst), c1 = lds128(cst + sel);
  float a2 = __uint_as_float(c0.x), th = __uint_as_float(c0.y);
  float eP = ex2f(a2 * gf);
  float e2 = eP * eP, e4 = e2 * e2, eQ = e4 * e4;
  float f2 = eQ * eQ, f4 = f2 * f2, f8 = f4 * f4, eR = f8 * f8;
  float pP = th * gf, pQ = pP * 8.f, pR = pP * 128.f;
  float Pr = eP * cosaf(pP), Pi = eP * sinaf(pP);
  float Qr = eQ * cosaf(pQ), Qi = eQ * sinaf(pQ);
  float Rr = eR * cosaf(pR), Ri = eR * sinaf(pR);
  uint32_t P1 = pack_h2(Pr, -Pi), P2 = pack_h2(Pi, Pr);
  uint32_t R1 = pack_h2(Rr, -Ri), R2 = pack_h2(Ri, Rr);
  uint32_t Q1 = pack_h2(Qr, Qi), Q2 = pack_h2(-Qi, Qr);
  q0 = Q1; q1 = hcmul(Q1, Q2, c1.y);
  av[0] = hcmul(P1, P2, c0.z);
  av[1] = hcmul(P1, P2, c0.w);
  av[2] = hcmul(R1, R2, c1.x);
  av[3] = hcmul(R1, R2, c1.z);
  av[4] = hcmul(R1, R2, c1.w);
}

__device__ __forceinline__ void put_near(uint32_t tab, int m, uint16_t v) {
  uint32_t a = tab + (TW_W + 32) * 4 + 4 * m;
  sts16(a, v); sts16(a + 6, v);
}

__device__ __forceinline__ void scatter(uint32_t tab, int p, float val) {
  uint16_t v = __bfloat16_as_ushort(__float2bfloat16_rn(val));
  if (p <= 512) {
    put_near(tab, p, v);
    if (p >= 256 && (p & 3) == 0) {
      put_near(tab, p + 1, v);
      if (p > 256) put_near(tab, p - 1, v);
      if (p == 512) put_near(tab, 514, v);
    }
  } else if (p < 1024) {
    int k = p >> 3;
    if (p & 4) sts16(tab + TW_3 * 4 + 2 * ((k & 1) ? k - 35 : k - 33), v);
    else       sts16(tab + TW_5 * 4 + 2 * ((k & 1) ? k - 32 : k - 34), v);
  } else if (p == 1024) {
    #pragma unroll
    for (int m = 1022; m <= 1028; m++) { uint32_t a = tab + TW_X * 4 + 4 * (m - 976); sts16(a, v); sts16(a + 6, v); }
  } else {
    int c = p >> 4;
    uint32_t a = tab + ((p & 8) ? TW_7 : TW_9) * 4 + 4 * (c - 50);
    sts16(a, v); sts16(a + 6, v);
  }
}

template <int S> __device__ __forceinline__ void near_step(float* d, uint32_t ua, uint32_t rm, uint32_t r0, uint32_t rp) {
  constexpr int i0 = (S < 16) ? 0 : (S < 32) ? 1 : (S < 35) ? 2 : (S == 63) ? 3 : 4;
  constexpr int arr = (S & 1) ? 0 : 2;
  constexpr int pos = ((S & 1) ? (1 - S) / 2 : -S / 2) + 8 * i0 + 8;
  uint64_t desc = mkdesc(ua + arr * UA_ARR + pos * 16, UA_ARR, 128);
  if constexpr (i0 == 0) wgmma_n64(d, r0, rp, rm, r0, desc);
  if constexpr (i0 == 1) wgmma_n56(d + 4, r0, rp, rm, r0, desc);
  if constexpr (i0 == 2) wgmma_n48(d + 8, r0, rp, rm, r0, desc);
  if constexpr (i0 == 3) wgmma_n40(d + 12, r0, rp, rm, r0, desc);
  if constexpr (i0 == 4) wgmma_n32(d + 16, r0, rp, rm, r0, desc);
}
__device__ __forceinline__ void wg_fence() { asm volatile("wgmma.fence.sync.aligned;" ::: "memory"); }
__device__ __forceinline__ void wg_commit() { asm volatile("wgmma.commit_group.sync.aligned;" ::: "memory"); }
template <int N> __device__ __forceinline__ void wg_wait() { asm volatile("wgmma.wait_group.sync.aligned %0;" :: "n"(N) : "memory"); }

template <int S0, int NS> __device__ __forceinline__ void near_batch(float* d, uint32_t ua, uint32_t wa) {
  uint32_t r[2 * NS + 1];
  #pragma unroll
  for (int i = 0; i < 2 * NS + 1; i++) r[i] = lds32(wa + (2 * S0 - 1 + i) * 32);
  wg_fence();
  near_step<S0>(d, ua, r[0], r[1], r[2]);
  if constexpr (NS > 1) near_step<S0 + 1>(d, ua, r[2], r[3], r[4]);
  if constexpr (NS > 2) near_step<S0 + 2>(d, ua, r[4], r[5], r[6]);
  if constexpr (NS > 3) near_step<S0 + 3>(d, ua, r[6], r[7], r[8]);
  wg_commit();
}

__global__ void __launch_bounds__(NTHR, 1)
ssm_gated_kernel(const __grid_constant__ CUtensorMap tmap_u, const Params P) {
  extern __shared__ __align__(1024) unsigned char smem[];
  const uint32_t sb = smem_u32(smem);
  const int tid = threadIdx.x, warp = tid >> 5, lane = tid & 31;
  const int g = lane >> 2, q = lane & 3;
  const int cta = blockIdx.x, c0 = cta * 4;
  const uint32_t mbar = sb + SM_BAR;

  if (tid == 0) {
    asm volatile("mbarrier.init.shared.b64 [%0], 1;" :: "r"(mbar));
    asm volatile("fence.proxy.async.shared::cta;" ::: "memory");
    asm volatile("mbarrier.arrive.expect_tx.shared.b64 _, [%0], %1;" :: "r"(mbar), "r"(32768) : "memory");
    #pragma unroll
    for (int i = 0; i < 8; i++)
      asm volatile("cp.async.bulk.tensor.2d.shared::cluster.global.mbarrier::complete_tx::bytes [%0], [%1, {%3, %4}], [%2];"
                   :: "r"(sb + SM_RAW + i * 4096), "l"((uint64_t)&tmap_u), "r"(mbar), "r"((cta >> 1) * 8), "r"(i * 256) : "memory");
  }
  float pr[4][6]; float ldt[4];
  const int kw = warp - 8, kbr = (kw >> 2) & 1, kpart = kw & 3;
  if (warp >= 8) {
    #pragma unroll
    for (int ch = 0; ch < 4; ch++) {
      int idx = (c0 + ch) * NMODE + kpart * 32 + lane;
      pr[ch][0] = ldbf(P.pm[kbr][0] + idx); pr[ch][1] = ldbf(P.pm[kbr][1] + idx);
      pr[ch][4] = ldbf(P.pm[kbr][4] + idx); pr[ch][5] = ldbf(P.pm[kbr][5] + idx);
      if (kbr == 0) { pr[ch][2] = ldbf(P.pm[0][2] + idx); pr[ch][3] = ldbf(P.pm[0][3] + idx); }
      else { pr[ch][2] = 2.f; pr[ch][3] = 0.f; }
      ldt[ch] = ldbf(P.logdt[kbr] + c0 + ch);
    }
  }
  uint4 gx[2][2], gwv[2];
  if (warp < 8) {
    #pragma unroll
    for (int r = 0; r < 2; r++) {
      const uint4* row = (const uint4*)(P.u + (size_t)(cta * 16 + warp * 2 + r) * DIM);
      gx[r][0] = __ldg(row + lane); gx[r][1] = __ldg(row + 32 + lane);
    }
    gwv[0] = __ldg((const uint4*)P.gate_w + lane); gwv[1] = __ldg((const uint4*)P.gate_w + 32 + lane);
  }
  for (int i = tid; i < (SM_CST - SM_UA) / 16; i += NTHR) sts128(sb + SM_UA + i * 16, 0, 0, 0, 0);
  __syncthreads();

  if (warp >= 8) {
    const uint32_t cst = sb + SM_CST + kw * 1536;
    const float gf = (float)g;
    const uint32_t sel = (g < 2) ? 32 : 16;
    const int kt = tid - 256;
    #pragma unroll 1
    for (int ch = 0; ch < 4; ch++) {
      float p0, p1, p2, p3, p4, p5, ld;
      p0 = pr[0][0]; p1 = pr[0][1]; p2 = pr[0][2]; p3 = pr[0][3]; p4 = pr[0][4]; p5 = pr[0][5]; ld = ldt[0];
      #pragma unroll
      for (int c = 1; c < 4; c++) if (ch == c) { p0 = pr[c][0]; p1 = pr[c][1]; p2 = pr[c][2]; p3 = pr[c][3]; p4 = pr[c][4]; p5 = pr[c][5]; ld = ldt[c]; }
      float dt = bf16_round(expf(ld));
      float are = kbr ? -bf16_round(expf(p0)) : p0;
      float a2 = (are * dt) * 1.4426950408889634f, th = p1 * dt;
      cf dB = {dt * p2, dt * p3}, C = {p4, p5};
      cf c = cmul(C, dB);
      float k0 = c.x, mx = fmaxf(fabsf(c.x), fabsf(c.y));
      #pragma unroll
      for (int o = 16; o; o >>= 1) { k0 += __shfl_xor_sync(~0u, k0, o); mx = fmaxf(mx, __shfl_xor_sync(~0u, mx, o)); }
      int e = (__float_as_uint(mx) >> 23) & 0xff; e = min(max(e, 1), 252);
      float sc = __uint_as_float((uint32_t)(253 - e) << 23), isc = __uint_as_float((uint32_t)(e + 1) << 23);
      c.x *= sc; c.y *= sc;
      cf w1 = cexp_fast(a2, th, 1.f), w64 = cexp_fast(a2, th, 64.f), w1024 = cexp_fast(a2, th, 1024.f);
      cf w2 = csq(w1), w4 = csq(w2), w8 = csq(w4), w128 = csq(w64), w256 = csq(w128);
      cf cw1 = cmul(c, w1), cw129 = cmul(cw1, w128), cw4 = cmul(c, w4), cw8 = cmul(c, w8), cw1032 = cmul(cw8, w1024);
      cf cw258 = cmul(cmul(c, w2), w256), cw262 = cmul(cw258, w4);
      uint32_t x1032 = pack_conj(cw1032), x64 = pack_h2(w64.x, w64.y);
      __syncwarp();
      uint32_t ce = cst + lane * 48;
      sts128(ce, __float_as_uint(a2), __float_as_uint(th), pack_conj(cw1), pack_conj(cw129));
      sts128(ce + 16, x1032, x64, pack_conj(cw4), pack_conj(cw8));
      sts128(ce + 32, x1032, x64, pack_conj(cw258), pack_conj(cw262));
      __syncwarp();
      float acc[5][4];
      #pragma unroll
      for (int t = 0; t < 5; t++) { acc[t][0] = acc[t][1] = acc[t][2] = acc[t][3] = 0.f; }
      #pragma unroll 1
      for (int ks = 0; ks < 4; ks++) {
        uint32_t a0, a1, a2r, a3, bA[5], bB[5];
        kgen_mode(cst + (ks * 8 + q) * 48, sel, gf, a0, a1, bA);
        kgen_mode(cst + (ks * 8 + q + 4) * 48, sel, gf, a2r, a3, bB);
        #pragma unroll
        for (int t = 0; t < 5; t++) mma_f16(acc[t], a0, a1, a2r, a3, bA[t], bB[t]);
      }
      const uint32_t pbuf = sb + SM_PART + (ch & 1) * 8 * PART_SZ;
      uint32_t pa = pbuf + kw * PART_SZ + (g * 8 + 2 * q) * 4;
      #pragma unroll
      for (int t = 0; t < 5; t++) {
        sts64f(pa + t * 512, acc[t][0] * isc, acc[t][1] * isc);
        sts64f(pa + t * 512 + 256, acc[t][2] * isc, acc[t][3] * isc);
      }
      if (lane == 0) sts32(pbuf + kw * PART_SZ + 640 * 4, __float_as_uint(k0));
      bar_sync(1, 256);
      {
        const int br = kt >> 7, r = kt & 127, j = r >> 3, col = r & 7;
        const uint32_t tab = sb + SM_TAB + (ch * 2 + br) * TAB_SZ;
        const uint32_t ra = pbuf + br * 4 * PART_SZ + r * 4;
        #pragma unroll
        for (int t = 0; t < 5; t++) {
          float v = (lds32f(ra + t * 512) + lds32f(ra + t * 512 + PART_SZ)) + (lds32f(ra + t * 512 + 2 * PART_SZ) + lds32f(ra + t * 512 + 3 * PART_SZ));
          int a = (t == 0) ? col + 1 : (t == 1) ? col + 129 : (t == 2) ? 128 * col + 1032
                : (t == 3) ? 128 * col + (col < 2 ? 258 : 4) : 128 * col + (col < 2 ? 262 : 8);
          scatter(tab, a + 8 * j, v);
        }
        if (r == 0) {
          uint32_t ka = pbuf + br * 4 * PART_SZ + 640 * 4;
          float v = (lds32f(ka) + lds32f(ka + PART_SZ)) + (lds32f(ka + 2 * PART_SZ) + lds32f(ka + 3 * PART_SZ));
          v += ldbf(P.dskip[br] + c0 + ch);
          scatter(tab, 0, v);
        }
      }
      bar_arrive(4 + ch, 256 + 128);
    }
  } else {
    const int wg = warp >> 2, br = (warp >> 1) & 1, w0 = warp & 1;
    #pragma unroll
    for (int r = 0; r < 2; r++) {
      float s = 0.f;
      #pragma unroll
      for (int h = 0; h < 2; h++) {
        const uint32_t* xv = (const uint32_t*)&gx[r][h]; const uint32_t* wv = (const uint32_t*)&gwv[h];
        #pragma unroll
        for (int i = 0; i < 4; i++) {
          __nv_bfloat162 pr2 = __hmul2(*(const __nv_bfloat162*)&xv[i], *(const __nv_bfloat162*)&wv[i]);
          uint32_t pv = *(uint32_t*)&pr2;
          s += bf_lo(pv); s += bf_hi(pv);
        }
      }
      #pragma unroll
      for (int o = 16; o; o >>= 1) s += __shfl_xor_sync(~0u, s, o);
      if (lane == 0) {
        float z = bf16_round(s);
        float gv = bf16_round(1.f / (1.f + expf(-z)));
        g_gate[cta * 16 + warp * 2 + r] = pack_bf2(gv, 1.f - gv);
        __threadfence();
      }
    }
    bar_sync(2, 256);
    unsigned int target = 0;
    if (tid == 0) { __threadfence(); unsigned int old = atomicAdd(&g_counter, 1u); target = (old / NCTA + 1u) * NCTA; }

    {
      uint32_t ok = 0; int it = 0;
      while (!ok && it++ < (1 << 22))
        asm volatile("{ .reg .pred p; mbarrier.try_wait.parity.shared.b64 p, [%1], 0; selp.u32 %0, 1, 0, p; }" : "=r"(ok) : "r"(mbar) : "memory");
    }
    {
      const int chs = (lane & 7) - (cta & 1) * 4;
      const int m = lane >> 3;
      #pragma unroll 2
      for (int it = 0; it < 8; it++) {
        int blk = warp * 8 + it;
        uint32_t r0, r1, r2, r3;
        ldsm4t(sb + SM_RAW + (blk * 32 + lane) * 16, r0, r1, r2, r3);
        uint32_t dst = ((unsigned)chs < 4u) ? sb + SM_UA + chs * UA_CH + m * UA_ARR + (blk + 8) * 16 : sb + SM_DUMMY;
        stsm4(dst, r0, r1, r2, r3);
      }
    }
    asm volatile("fence.proxy.async.shared::cta;" ::: "memory");
    bar_sync(2, 256);
    for (int it = tid; it < 4 * 192; it += 256) {
      int ch = it / 192, chi = it % 192 - 1;
      uint32_t ub = sb + SM_UA + ch * UA_CH + 8 * 16;
      auto chunk_addr = [&](int c) { return ub + (c & 3) * UA_ARR + (c >> 2) * 16; };
      uint4 a = lds128(chunk_addr(chi - 1)), b = lds128(chunk_addr(chi)), c = lds128(chunk_addr(chi + 1));
      float v[17] = {bf_hi(a.y), bf_lo(a.z), bf_hi(a.z), bf_lo(a.w), bf_hi(a.w),
                     bf_lo(b.x), bf_hi(b.x), bf_lo(b.y), bf_hi(b.y), bf_lo(b.z), bf_hi(b.z), bf_lo(b.w), bf_hi(b.w),
                     bf_lo(c.x), bf_hi(c.x), bf_lo(c.y), bf_hi(c.y)};
      float s3[12], f5[8], f7[8], f9[8];
      #pragma unroll
      for (int i = 0; i < 12; i++) s3[i] = (v[i] + v[i + 1]) + v[i + 2];
      #pragma unroll
      for (int i = 0; i < 8; i++) {
        f5[i] = s3[i + 4] + (v[i + 3] + v[i + 7]);
        f7[i] = f5[i] + (v[i + 2] + v[i + 8]);
        f9[i] = f7[i] + (v[i + 1] + v[i + 9]);
      }
      uint32_t fb = sb + SM_FS + ch * FS_CH;
      sts128(fb + F5_OFF + (chi + 2) * 16, pack_bf2(f5[0], f5[1]), pack_bf2(f5[2], f5[3]), pack_bf2(f5[4], f5[5]), pack_bf2(f5[6], f5[7]));
      sts128(fb + F3_OFF + (chi + 1) * 16, pack_bf2(s3[0], s3[1]), pack_bf2(s3[2], s3[3]), pack_bf2(s3[4], s3[5]), pack_bf2(s3[6], s3[7]));
      if (chi <= 125) { int x = chi + 2; sts128(fb + F9_OFF + (x & 1) * 1024 + (x >> 1) * 16, pack_bf2(f9[0], f9[1]), pack_bf2(f9[2], f9[3]), pack_bf2(f9[4], f9[5]), pack_bf2(f9[6], f9[7])); }
      if (chi <= 126) { int x = chi + 1; sts128(fb + F7_OFF + (x & 1) * 1024 + (x >> 1) * 16, pack_bf2(f7[0], f7[1]), pack_bf2(f7[2], f7[3]), pack_bf2(f7[4], f7[5]), pack_bf2(f7[6], f7[7])); }
    }
    if (tid < 4) {
      uint32_t ub = sb + SM_UA + tid * UA_CH + 8 * 16;
      uint4 a = lds128(ub + 2 * UA_ARR + 47 * 16), b = lds128(ub + 3 * UA_ARR + 47 * 16);
      float v[10] = {bf_hi(a.y), bf_lo(a.z), bf_hi(a.z), bf_lo(a.w), bf_hi(a.w), bf_lo(b.x), bf_hi(b.x), bf_lo(b.y), bf_hi(b.y), bf_lo(b.z)};
      float s3[8];
      #pragma unroll
      for (int i = 0; i < 8; i++) s3[i] = (v[i] + v[i + 1]) + v[i + 2];
      sts128(sb + SM_FS + tid * FS_CH + F3_OFF + 192 * 16, pack_bf2(s3[0], s3[1]), pack_bf2(s3[2], s3[3]), pack_bf2(s3[4], s3[5]), pack_bf2(s3[6], s3[7]));
    }
    if (tid == 0) {
      int it = 0; unsigned int v;
      do { asm volatile("ld.acquire.gpu.global.u32 %0, [%1];" : "=r"(v) : "l"(&g_counter) : "memory"); } while ((int)(v - target) < 0 && ++it < (1 << 22));
    }
    bar_sync(2, 256);
    for (int i = tid; i < 1024; i += 256) {
      int t2 = i >> 5, v = i & 31;
      uint32_t x = __ldcg(&g_gate[64 * t2 + v]), y = __ldcg(&g_gate[64 * t2 + 32 + v]);
      sts32(sb + SM_GW + (t2 * 40 + v) * 4, __byte_perm(x, y, 0x5410));
      sts32(sb + SM_GW + 5120 + (t2 * 40 + v) * 4, __byte_perm(x, y, 0x7632));
    }
    bar_sync(2, 256);

    #pragma unroll 1
    for (int cc = 0; cc < 2; cc++) {
      const int ch = wg + 2 * cc;
      const uint32_t tab = sb + SM_TAB + (ch * 2 + br) * TAB_SZ;
      const uint32_t ua = sb + SM_UA + ch * UA_CH;
      float d[32];
      #pragma unroll
      for (int i = 0; i < 32; i++) d[i] = 0.f;
      bar_sync(4 + ch, 256 + 128);
      const int e0 = 16 * w0 + g - 2 * q - 16;
      const uint32_t wa = tab + (TW_W + 32 + e0) * 4;
      near_batch<0, 4>(d, ua, wa);
      near_batch<4, 4>(d, ua, wa);  wg_wait<1>();
      near_batch<8, 4>(d, ua, wa);  wg_wait<1>();
      near_batch<12, 4>(d, ua, wa); wg_wait<1>();
      near_batch<16, 4>(d, ua, wa); wg_wait<1>();
      near_batch<20, 4>(d, ua, wa); wg_wait<1>();
      near_batch<24, 4>(d, ua, wa); wg_wait<1>();
      near_batch<28, 4>(d, ua, wa); wg_wait<1>();
      near_batch<32, 3>(d, ua, wa); wg_wait<1>();
      const uint32_t wx = tab + (TW_X - 976 + e0) * 4;
      near_batch<63, 1>(d, ua, wx); wg_wait<1>();
      near_batch<64, 3>(d, ua, wx);
      wg_wait<0>();
      const uint32_t fb = sb + SM_FS + ch * FS_CH;
      {
        uint32_t b5[6][2], b3[6][2];
        const uint32_t a5 = tab + TW_5 * 4 + ((48 + 4 * g - 2 * q + 2 * w0 + 2 - 34) >> 1) * 4;
        const uint32_t a3 = tab + TW_3 * 4 + ((48 + 4 * g - 2 * q + 2 * w0 + 1 - 35) >> 1) * 4;
        #pragma unroll
        for (int dl = 0; dl < 6; dl++) {
          b5[dl][0] = lds32(a5 + dl * 32); b5[dl][1] = lds32(a5 + dl * 32 - 16);
          b3[dl][0] = lds32(a3 + dl * 32); b3[dl][1] = lds32(a3 + dl * 32 - 16);
        }
        const int m = lane >> 3;
        const uint32_t la = fb + ((lane & 7) + (m & 1) + (m >> 1) * 8) * 16;
        #pragma unroll
        for (int kap = 0; kap < 12; kap++) {
          uint32_t x0, x1, x2, x3, y0, y1, y2, y3;
          ldsm4t(la + F5_OFF + kap * 256, x0, x1, x2, x3);
          ldsm4t(la + F3_OFF + kap * 256, y0, y1, y2, y3);
          #pragma unroll
          for (int i = 2; i < 8; i++) {
            const int dl = 2 * i - kap;
            if (dl >= 3 && dl <= 8) {
              mma_bf16(d + 4 * i, x0, x1, x2, x3, b5[dl - 3][0], b5[dl - 3][1]);
              mma_bf16(d + 4 * i, y0, y1, y2, y3, b3[dl - 3][0], b3[dl - 3][1]);
            }
          }
        }
      }
      {
        uint32_t b9[4][2], b7[4][2];
        const uint32_t a9 = tab + TW_9 * 4 + (64 + 2 * g - 2 * q + w0 + 1 - 50) * 4;
        const uint32_t a7 = tab + TW_7 * 4 + (64 + 2 * g - 2 * q + w0 - 50) * 4;
        #pragma unroll
        for (int dl = 0; dl < 4; dl++) {
          b9[dl][0] = lds32(a9 + dl * 64); b9[dl][1] = lds32(a9 + dl * 64 - 32);
          b7[dl][0] = lds32(a7 + dl * 64); b7[dl][1] = lds32(a7 + dl * 64 - 32);
        }
        const int m = lane >> 3;
        const uint32_t la = fb + (m & 1) * 1024 + ((lane & 7) + (m >> 1) * 8) * 16;
        #pragma unroll
        for (int kap = 0; kap < 4; kap++) {
          uint32_t x0, x1, x2, x3, y0, y1, y2, y3;
          ldsm4t(la + F9_OFF + kap * 256, x0, x1, x2, x3);
          ldsm4t(la + F7_OFF + kap * 256, y0, y1, y2, y3);
          #pragma unroll
          for (int i = 4; i < 8; i++) {
            const int dl = i - kap;
            if (dl >= 4) {
              mma_bf16(d + 4 * i, x0, x1, x2, x3, b9[dl - 4][0], b9[dl - 4][1]);
              mma_bf16(d + 4 * i, y0, y1, y2, y3, b7[dl - 4][0], b7[dl - 4][1]);
            }
          }
        }
      }
      {
        const uint32_t ga = sb + SM_GW + br * 5120 + (q * 40 + 16 * w0 + g) * 4;
        const uint32_t tb = sb + SM_RAW + (br * 4 + ch) * 4096;
        const int m = lane >> 3, j = lane & 7;
        #pragma unroll
        for (int i = 0; i < 8; i += 2) {
          uint32_t r[4];
          #pragma unroll
          for (int k = 0; k < 4; k++) {
            const int ii = i + (k >> 1), h = k & 1;
            uint32_t y = pack_bf2(d[4 * ii + 2 * h], d[4 * ii + 2 * h + 1]);
            uint32_t gw = lds32(ga + (ii * 160 + 8 * h) * 4);
            __nv_bfloat162 t2 = __hmul2(*(__nv_bfloat162*)&y, *(__nv_bfloat162*)&gw);
            r[k] = *(uint32_t*)&t2;
          }
          int chi = 4 * (8 * (i + (m >> 1)) + j) + 2 * w0 + (m & 1);
          stsm4t(tb + (chi ^ ((chi >> 3) & 3)) * 16, r[0], r[1], r[2], r[3]);
        }
      }
    }
  }
  __syncthreads();
  {
    const int m = lane >> 3, j = lane & 7;
    #pragma unroll 2
    for (int it = 0; it < 4; it++) {
      int cb = (warp * 4 + it) * 4;
      int chi = cb + (m >> 1) * 2 + (j >> 2);
      uint32_t r0, r1, r2, r3;
      ldsm4t(sb + SM_RAW + ((m & 1) * 4 + (j & 3)) * 4096 + (chi ^ ((chi >> 3) & 3)) * 16, r0, r1, r2, r3);
      __nv_bfloat162 o0 = __hadd2(*(__nv_bfloat162*)&r0, *(__nv_bfloat162*)&r1);
      __nv_bfloat162 o1 = __hadd2(*(__nv_bfloat162*)&r2, *(__nv_bfloat162*)&r3);
      int l = (cb + (q >> 1)) * 8 + g;
      __nv_bfloat162* op = (__nv_bfloat162*)(P.out + (size_t)l * DIM + c0 + (q & 1) * 2);
      op[0] = o0;
      op[(size_t)16 * DIM / 2] = o1;
    }
  }
}

typedef CUresult (*EncodeFn)(CUtensorMap*, CUtensorMapDataType, cuuint32_t, void*, const cuuint64_t*, const cuuint64_t*,
                             const cuuint32_t*, const cuuint32_t*, CUtensorMapInterleave, CUtensorMapSwizzle,
                             CUtensorMapL2promotion, CUtensorMapFloatOOBfill);
}

extern "C" void kernel_launch(void* const* d_in, const int* in_sizes, int n_in, void* d_out, int out_size) {
  (void)in_sizes; (void)n_in; (void)out_size;
  static EncodeFn enc = nullptr;
  if (!enc) {
    void* fn = nullptr; cudaDriverEntryPointQueryResult qr;
    cudaGetDriverEntryPoint("cuTensorMapEncodeTiled", &fn, cudaEnableDefault, &qr);
    enc = (EncodeFn)fn;
    cudaFuncSetAttribute(ssm_gated_kernel, cudaFuncAttributeMaxDynamicSharedMemorySize, SM_TOTAL);
  }
  CUtensorMap tm;
  cuuint64_t gd[2] = {(cuuint64_t)DIM, (cuuint64_t)SEQ}; cuuint64_t gs[1] = {(cuuint64_t)DIM * 2};
  cuuint32_t bd[2] = {8, 256}; cuuint32_t es[2] = {1, 1};
  enc(&tm, CU_TENSOR_MAP_DATA_TYPE_BFLOAT16, 2, d_in[0], gd, gs, bd, es, CU_TENSOR_MAP_INTERLEAVE_NONE,
      CU_TENSOR_MAP_SWIZZLE_NONE, CU_TENSOR_MAP_L2_PROMOTION_L2_128B, CU_TENSOR_MAP_FLOAT_OOB_FILL_NONE);
  Params P;
  typedef const __nv_bfloat16* bp;
  P.u = (bp)d_in[0];
  for (int i = 0; i < 6; i++) P.pm[0][i] = (bp)d_in[1 + i];
  P.logdt[0] = (bp)d_in[7]; P.dskip[0] = (bp)d_in[8];
  P.pm[1][0] = (bp)d_in[10]; P.pm[1][1] = (bp)d_in[11]; P.pm[1][2] = nullptr; P.pm[1][3] = nullptr;
  P.pm[1][4] = (bp)d_in[12]; P.pm[1][5] = (bp)d_in[13];
  P.logdt[1] = (bp)d_in[14]; P.dskip[1] = (bp)d_in[15];
  P.gate_w = (bp)d_in[16];
  P.out = (__nv_bfloat16*)d_out;
  ssm_gated_kernel<<<NCTA, NTHR, SM_TOTAL, cudaStreamPerThread>>>(tm, P);
}
```

```cpp
#include <cuda_runtime.h>
#include <cuda_bf16.h>
#include <cuda_fp16.h>
#include <cuda.h>
#include <stdint.h>

#define STAMP(i) do {} while (0)
#define STAMP_EXTRA 0
#define STAMP_DUMP() do {} while (0)

#define STG 1
namespace {

constexpr int SEQ = 2048, DIM = 512, NMODE = 128;
constexpr int NCTA = 128, NTHR = 768;

constexpr int GSLOT   = 3584;
constexpr int GBUF    = 16 * GSLOT;
constexpr int Y2_OFF = 80 * 4, Y3_OFF = (80 + 1728 + 144) * 4, Y_CH = (80 + 1728 + 144 + 1152) * 4;
constexpr int SM_G    = 0;
constexpr int SM_T    = 0;
constexpr int SM_T3   = SM_T + 32768;
constexpr int SM_RX   = SM_T3 + 16384;
constexpr int SM_Y23  = 16 * GSLOT + 1024;
constexpr int SM_RAW  = 2 * GBUF;
constexpr int SM_GW   = SM_RAW, SM_GE = SM_RAW + 10240;
constexpr int XS_CH   = 4 * 512 + 16;
constexpr int SM_XS   = SM_RAW + 16384;
constexpr int UA_ARR  = 74 * 16;
constexpr int UA_CH   = 4 * UA_ARR + 16;
constexpr int SM_UA   = SM_XS + 8320;
constexpr int TW_W = 32, TW_X = 576, TW_2 = 656, TW_3 = 736, TW_TOT = 816;
constexpr int TAB_SZ  = TW_TOT * 4;
constexpr int SM_TAB  = SM_UA + 4 * UA_CH;
constexpr int SM_Y01  = SM_TAB + 8 * TAB_SZ;
constexpr int SM_ROW  = SM_Y01;
constexpr int SM_PRM  = SM_Y01 + 2 * Y_CH;
constexpr int SM_MX   = SM_PRM + 10240 + 64;
constexpr int SM_BAR  = SM_MX + 128;
constexpr int SM_TOTAL = SM_BAR + 256;
constexpr int MB_PRM = 0, MB_U = 8, MB_PEER = 16, MB_URDY = 24, MB_ROW = 32, MB_G1 = 40, MB_GW = 48, MB_G23 = 56, MB_Y = 64  , MB_LOC = 96, MB_RX = 160;
static_assert(SM_TOTAL + STAMP_EXTRA <= 232448, "smem");
static_assert(1024 + Y_CH <= 8 * GSLOT && SM_RX + 8192 <= GBUF, "alias");
static_assert(SM_UA % 128 == 0 && SM_XS % 128 == 0 && SM_TAB % 16 == 0 && SM_Y01 % 16 == 0 && Y_CH % 16 == 0 && SM_T % 128 == 0, "align");

__device__ uint32_t g_gate[SEQ];
__device__ uint32_t g_epoch[NCTA];

struct Params {
  const __nv_bfloat16* u;
  const __nv_bfloat16* pm[10];
  const __nv_bfloat16* pv[4];
  const __nv_bfloat16* gate_w;
  __nv_bfloat16* out;
};

__device__ __forceinline__ void wgmma_n32(float* d, const uint32_t* a, uint64_t desc) {
  asm volatile("wgmma.mma_async.sync.aligned.m64n32k16.f32.bf16.bf16 {%0, %1, %2, %3, %4, %5, %6, %7, %8, %9, %10, %11, %12, %13, %14, %15}, {%16, %17, %18, %19}, %20, 1, 1, 1, 0;\n"
    : "+f"(d[0]), "+f"(d[1]), "+f"(d[2]), "+f"(d[3]), "+f"(d[4]), "+f"(d[5]), "+f"(d[6]), "+f"(d[7]), "+f"(d[8]), "+f"(d[9]), "+f"(d[10]), "+f"(d[11]), "+f"(d[12]), "+f"(d[13]), "+f"(d[14]), "+f"(d[15])
    : "r"(a[0]), "r"(a[1]), "r"(a[2]), "r"(a[3]), "l"(desc));
}

__device__ __forceinline__ void wgmma_n40(float* d, const uint32_t* a, uint64_t desc) {
  asm volatile("wgmma.mma_async.sync.aligned.m64n40k16.f32.bf16.bf16 {%0, %1, %2, %3, %4, %5, %6, %7, %8, %9, %10, %11, %12, %13, %14, %15, %16, %17, %18, %19}, {%20, %21, %22, %23}, %24, 1, 1, 1, 0;\n"
    : "+f"(d[0]), "+f"(d[1]), "+f"(d[2]), "+f"(d[3]), "+f"(d[4]), "+f"(d[5]), "+f"(d[6]), "+f"(d[7]), "+f"(d[8]), "+f"(d[9]), "+f"(d[10]), "+f"(d[11]), "+f"(d[12]), "+f"(d[13]), "+f"(d[14]), "+f"(d[15]), "+f"(d[16]), "+f"(d[17]), "+f"(d[18]), "+f"(d[19])
    : "r"(a[0]), "r"(a[1]), "r"(a[2]), "r"(a[3]), "l"(desc));
}

__device__ __forceinline__ void wgmma_n48(float* d, const uint32_t* a, uint64_t desc) {
  asm volatile("wgmma.mma_async.sync.aligned.m64n48k16.f32.bf16.bf16 {%0, %1, %2, %3, %4, %5, %6, %7, %8, %9, %10, %11, %12, %13, %14, %15, %16, %17, %18, %19, %20, %21, %22, %23}, {%24, %25, %26, %27}, %28, 1, 1, 1, 0;\n"
    : "+f"(d[0]), "+f"(d[1]), "+f"(d[2]), "+f"(d[3]), "+f"(d[4]), "+f"(d[5]), "+f"(d[6]), "+f"(d[7]), "+f"(d[8]), "+f"(d[9]), "+f"(d[10]), "+f"(d[11]), "+f"(d[12]), "+f"(d[13]), "+f"(d[14]), "+f"(d[15]), "+f"(d[16]), "+f"(d[17]), "+f"(d[18]), "+f"(d[19]), "+f"(d[20]), "+f"(d[21]), "+f"(d[22]), "+f"(d[23])
    : "r"(a[0]), "r"(a[1]), "r"(a[2]), "r"(a[3]), "l"(desc));
}

__device__ __forceinline__ void wgmma_n56(float* d, const uint32_t* a, uint64_t desc) {
  asm volatile("wgmma.mma_async.sync.aligned.m64n56k16.f32.bf16.bf16 {%0, %1, %2, %3, %4, %5, %6, %7, %8, %9, %10, %11, %12, %13, %14, %15, %16, %17, %18, %19, %20, %21, %22, %23, %24, %25, %26, %27}, {%28, %29, %30, %31}, %32, 1, 1, 1, 0;\n"
    : "+f"(d[0]), "+f"(d[1]), "+f"(d[2]), "+f"(d[3]), "+f"(d[4]), "+f"(d[5]), "+f"(d[6]), "+f"(d[7]), "+f"(d[8]), "+f"(d[9]), "+f"(d[10]), "+f"(d[11]), "+f"(d[12]), "+f"(d[13]), "+f"(d[14]), "+f"(d[15]), "+f"(d[16]), "+f"(d[17]), "+f"(d[18]), "+f"(d[19]), "+f"(d[20]), "+f"(d[21]), "+f"(d[22]), "+f"(d[23]), "+f"(d[24]), "+f"(d[25]), "+f"(d[26]), "+f"(d[27])
    : "r"(a[0]), "r"(a[1]), "r"(a[2]), "r"(a[3]), "l"(desc));
}

__device__ __forceinline__ void wgmma_n64(float* d, const uint32_t* a, uint64_t desc) {
  asm volatile("wgmma.mma_async.sync.aligned.m64n64k16.f32.bf16.bf16 {%0, %1, %2, %3, %4, %5, %6, %7, %8, %9, %10, %11, %12, %13, %14, %15, %16, %17, %18, %19, %20, %21, %22, %23, %24, %25, %26, %27, %28, %29, %30, %31}, {%32, %33, %34, %35}, %36, 1, 1, 1, 0;\n"
    : "+f"(d[0]), "+f"(d[1]), "+f"(d[2]), "+f"(d[3]), "+f"(d[4]), "+f"(d[5]), "+f"(d[6]), "+f"(d[7]), "+f"(d[8]), "+f"(d[9]), "+f"(d[10]), "+f"(d[11]), "+f"(d[12]), "+f"(d[13]), "+f"(d[14]), "+f"(d[15]), "+f"(d[16]), "+f"(d[17]), "+f"(d[18]), "+f"(d[19]), "+f"(d[20]), "+f"(d[21]), "+f"(d[22]), "+f"(d[23]), "+f"(d[24]), "+f"(d[25]), "+f"(d[26]), "+f"(d[27]), "+f"(d[28]), "+f"(d[29]), "+f"(d[30]), "+f"(d[31])
    : "r"(a[0]), "r"(a[1]), "r"(a[2]), "r"(a[3]), "l"(desc));
}

__device__ __forceinline__ void wgmma_ss48(float* d, uint64_t da, uint64_t db) {
  asm volatile("wgmma.mma_async.sync.aligned.m64n48k16.f32.f16.f16 {%0,%1,%2,%3,%4,%5,%6,%7,%8,%9,%10,%11,%12,%13,%14,%15,%16,%17,%18,%19,%20,%21,%22,%23}, %24, %25, 1, 1, 1, 1, 1;\n"
    : "+f"(d[0]),"+f"(d[1]),"+f"(d[2]),"+f"(d[3]),"+f"(d[4]),"+f"(d[5]),"+f"(d[6]),"+f"(d[7]),"+f"(d[8]),"+f"(d[9]),"+f"(d[10]),"+f"(d[11]),
      "+f"(d[12]),"+f"(d[13]),"+f"(d[14]),"+f"(d[15]),"+f"(d[16]),"+f"(d[17]),"+f"(d[18]),"+f"(d[19]),"+f"(d[20]),"+f"(d[21]),"+f"(d[22]),"+f"(d[23])
    : "l"(da), "l"(db));
}
__device__ __forceinline__ uint32_t smem_u32(const void* p) { return (uint32_t)__cvta_generic_to_shared(p); }
__device__ __forceinline__ uint64_t mkdesc(uint32_t addr, uint32_t lbo, uint32_t sbo) {
  return (uint64_t)((addr & 0x3FFFF) >> 4) | ((uint64_t)(lbo >> 4) << 16) | ((uint64_t)(sbo >> 4) << 32);
}
__device__ __forceinline__ uint32_t lds32(uint32_t a) { uint32_t v; asm volatile("ld.shared.u32 %0, [%1];" : "=r"(v) : "r"(a) : "memory"); return v; }
__device__ __forceinline__ uint4 lds128(uint32_t a) { uint4 v; asm volatile("ld.shared.v4.u32 {%0,%1,%2,%3}, [%4];" : "=r"(v.x), "=r"(v.y), "=r"(v.z), "=r"(v.w) : "r"(a) : "memory"); return v; }
__device__ __forceinline__ float ldsbf(uint32_t a) { uint16_t v; asm volatile("ld.shared.u16 %0, [%1];" : "=h"(v) : "r"(a) : "memory"); return __uint_as_float((uint32_t)v << 16); }
__device__ __forceinline__ void sts16(uint32_t a, uint32_t v) { asm volatile("st.shared.u16 [%0], %1;" :: "r"(a), "h"((uint16_t)v) : "memory"); }
__device__ __forceinline__ void sts32(uint32_t a, uint32_t v) { asm volatile("st.shared.u32 [%0], %1;" :: "r"(a), "r"(v) : "memory"); }
__device__ __forceinline__ void sts128(uint32_t a, uint32_t x, uint32_t y, uint32_t z, uint32_t w) { asm volatile("st.shared.v4.u32 [%0], {%1,%2,%3,%4};" :: "r"(a), "r"(x), "r"(y), "r"(z), "r"(w) : "memory"); }
__device__ __forceinline__ void ldsm4t(uint32_t a, uint32_t* r) {
  asm volatile("ldmatrix.sync.aligned.m8n8.x4.trans.shared.b16 {%0,%1,%2,%3}, [%4];" : "=r"(r[0]), "=r"(r[1]), "=r"(r[2]), "=r"(r[3]) : "r"(a) : "memory");
}
__device__ __forceinline__ void stsm4(uint32_t a, const uint32_t* r) {
  asm volatile("stmatrix.sync.aligned.m8n8.x4.shared.b16 [%0], {%1,%2,%3,%4};" :: "r"(a), "r"(r[0]), "r"(r[1]), "r"(r[2]), "r"(r[3]) : "memory");
}
__device__ __forceinline__ void stsm4t(uint32_t a, const uint32_t* r) {
  asm volatile("stmatrix.sync.aligned.m8n8.x4.trans.shared.b16 [%0], {%1,%2,%3,%4};" :: "r"(a), "r"(r[0]), "r"(r[1]), "r"(r[2]), "r"(r[3]) : "memory");
}
__device__ __forceinline__ void mma_bf16(float* c, uint32_t a0, uint32_t a1, uint32_t a2, uint32_t a3, const uint32_t* b) {
  asm volatile("mma.sync.aligned.m16n8k16.row.col.f32.bf16.bf16.f32 {%0,%1,%2,%3}, {%4,%5,%6,%7}, {%8,%9}, {%0,%1,%2,%3};"
    : "+f"(c[0]), "+f"(c[1]), "+f"(c[2]), "+f"(c[3]) : "r"(a0), "r"(a1), "r"(a2), "r"(a3), "r"(b[0]), "r"(b[1]));
}
__device__ __forceinline__ void bar_sync(int id, int n) { asm volatile("bar.sync %0, %1;" :: "r"(id), "r"(n) : "memory"); }
__device__ __forceinline__ void bar_arrive(int id, int n) { asm volatile("bar.arrive %0, %1;" :: "r"(id), "r"(n) : "memory"); }
__device__ __forceinline__ float ex2f(float x) { float y; asm("ex2.approx.ftz.f32 %0, %1;" : "=f"(y) : "f"(x)); return y; }
__device__ __forceinline__ float sinaf(float x) { float y; asm("sin.approx.ftz.f32 %0, %1;" : "=f"(y) : "f"(x)); return y; }
__device__ __forceinline__ float cosaf(float x) { float y; asm("cos.approx.ftz.f32 %0, %1;" : "=f"(y) : "f"(x)); return y; }
__device__ __forceinline__ uint32_t pack_h2(float lo, float hi) { uint32_t r; asm("cvt.rn.f16x2.f32 %0, %1, %2;" : "=r"(r) : "f"(hi), "f"(lo)); return r; }
__device__ __forceinline__ uint32_t pack_bf2(float lo, float hi) { uint32_t r; asm("cvt.rn.bf16x2.f32 %0, %1, %2;" : "=r"(r) : "f"(hi), "f"(lo)); return r; }
__device__ __forceinline__ float bf_lo(uint32_t v) { return __uint_as_float(v << 16); }
__device__ __forceinline__ float bf_hi(uint32_t v) { return __uint_as_float(v & 0xffff0000u); }
__device__ __forceinline__ float bf16_round(float x) { return __bfloat162float(__float2bfloat16_rn(x)); }
__device__ __forceinline__ uint32_t hadd(uint32_t a, uint32_t b) { __nv_bfloat162 r = __hadd2(*(__nv_bfloat162*)&a, *(__nv_bfloat162*)&b); return *(uint32_t*)&r; }
__device__ __forceinline__ float exp_acc(float x) {
  const float L = 1.4426950408889634f, Ll = 1.9259629911266175e-8f;
  float t = x * L, r = fmaf(x, L, -t); r = fmaf(x, Ll, r);
  return ex2f(t) * fmaf(r, 0.6931471805599453f, 1.f);
}
__device__ __forceinline__ void mbar_init(uint32_t a, int n) { asm volatile("mbarrier.init.shared.b64 [%0], %1;" :: "r"(a), "r"(n)); }
__device__ __forceinline__ void mbar_arrive(uint32_t a) { asm volatile("mbarrier.arrive.shared.b64 _, [%0];" :: "r"(a) : "memory"); }
__device__ __forceinline__ void mbar_expect(uint32_t a, int bytes) { asm volatile("mbarrier.arrive.expect_tx.shared.b64 _, [%0], %1;" :: "r"(a), "r"(bytes) : "memory"); }
__device__ __forceinline__ void mbar_wait(uint32_t a) {
  uint32_t ok = 0; int it = 0;
  while (!ok && it++ < (1 << 20))
    asm volatile("{ .reg .pred p; mbarrier.try_wait.parity.shared.b64 p, [%1], 0, 2000; selp.u32 %0, 1, 0, p; }" : "=r"(ok) : "r"(a) : "memory");
}
__device__ __forceinline__ void warp_arrive(uint32_t a, int lane) { __syncwarp(); if (lane == 0) mbar_arrive(a); }
__device__ __forceinline__ void fence_async() { asm volatile("fence.proxy.async.shared::cta;" ::: "memory"); }
__device__ __forceinline__ uint32_t mapa(uint32_t a, uint32_t rank) { uint32_t r; asm("mapa.shared::cluster.u32 %0, %1, %2;" : "=r"(r) : "r"(a), "r"(rank)); return r; }
__device__ __forceinline__ void dsmem_copy(uint32_t dst, uint32_t src, int bytes, uint32_t mb) {
  asm volatile("cp.async.bulk.shared::cluster.shared::cta.mbarrier::complete_tx::bytes [%0], [%1], %2, [%3];" :: "r"(dst), "r"(src), "r"(bytes), "r"(mb) : "memory");
}
__device__ __forceinline__ void bulk_g2s(uint32_t dst, const void* src, int bytes, uint32_t mb) {
  asm volatile("cp.async.bulk.shared::cluster.global.mbarrier::complete_tx::bytes [%0], [%1], %2, [%3];" :: "r"(dst), "l"(src), "r"(bytes), "r"(mb) : "memory");
}
__device__ __forceinline__ void wg_fence() { asm volatile("wgmma.fence.sync.aligned;" ::: "memory"); }
__device__ __forceinline__ void wg_commit() { asm volatile("wgmma.commit_group.sync.aligned;" ::: "memory"); }
template <int N> __device__ __forceinline__ void wg_wait() { asm volatile("wgmma.wait_group.sync.aligned %0;" :: "n"(N) : "memory"); }
template <int N> __device__ __forceinline__ void fence_acc(float* d) {
  #pragma unroll
  for (int i = 0; i < N; i++) asm volatile("" : "+f"(d[i]) :: "memory");
}
__device__ __forceinline__ uint32_t rcopy(uint32_t x) { uint32_t y; asm volatile("mov.b32 %0, %1;" : "=r"(y) : "r"(x)); return y; }

struct cf { float x, y; };
__device__ __forceinline__ cf cmul(cf a, cf b) { cf r; r.x = a.x * b.x - a.y * b.y; r.y = a.x * b.y + a.y * b.x; return r; }
__device__ __forceinline__ cf cmulc(cf a, cf b) { cf r; r.x = a.x * b.x + a.y * b.y; r.y = a.y * b.x - a.x * b.y; return r; }
__device__ __forceinline__ cf csub(cf a, cf b) { cf r; r.x = a.x - b.x; r.y = a.y - b.y; return r; }
__device__ __forceinline__ cf csq(cf a) { cf r; r.x = a.x * a.x - a.y * a.y; r.y = (a.x + a.x) * a.y; return r; }
__device__ __forceinline__ cf cexp_fast(float a2, float th, float x) {
  float e = ex2f(a2 * x), ph = th * x; cf r; r.x = e * cosaf(ph); r.y = e * sinaf(ph); return r;
}
struct hp { uint32_t r, i; };
__device__ __forceinline__ hp hbro(cf m) { hp h; h.r = pack_h2(m.x, m.x); h.i = pack_h2(m.y, m.y); return h; }
template <bool CONJ> __device__ __forceinline__ hp hmul(hp a, hp m) {
  const __half2 ar = *(__half2*)&a.r, ai = *(__half2*)&a.i, mr = *(__half2*)&m.r, mi = CONJ ? __hneg2(*(__half2*)&m.i) : *(__half2*)&m.i;
  const __half2 x = __hfma2(ar, mr, __hneg2(__hmul2(ai, mi))), y = __hfma2(ar, mi, __hmul2(ai, mr));
  hp o; o.r = *(uint32_t*)&x; o.i = *(uint32_t*)&y; return o;
}
__device__ __forceinline__ hp hlo(hp a, hp b) { hp o; o.r = __byte_perm(a.r, b.r, 0x5410); o.i = __byte_perm(a.i, b.i, 0x5410); return o; }
__device__ __forceinline__ void put4(uint32_t a, hp p0, hp p1, hp p2, hp p3) {
  sts128(a, p0.r, p1.r, p2.r, p3.r); sts128(a + 128, p0.i, p1.i, p2.i, p3.i);
}
__device__ __forceinline__ void put8(uint32_t a, const cf* v) {
  sts128(a, pack_h2(v[0].x, v[1].x), pack_h2(v[2].x, v[3].x), pack_h2(v[4].x, v[5].x), pack_h2(v[6].x, v[7].x));
  sts128(a + 128, pack_h2(v[0].y, v[1].y), pack_h2(v[2].y, v[3].y), pack_h2(v[4].y, v[5].y), pack_h2(v[6].y, v[7].y));
}
__device__ __forceinline__ void put8_mul(uint32_t a, const uint32_t* tr, const uint32_t* ti, cf m) {
  uint32_t mr = pack_h2(m.x, m.x), mi = pack_h2(m.y, m.y);
  const __half2 hr = *(__half2*)&mr, hi = *(__half2*)&mi;
  uint32_t o[8];
  #pragma unroll
  for (int i = 0; i < 4; i++) {
    const __half2 r = *(const __half2*)&tr[i], s = *(const __half2*)&ti[i];
    __half2 x = __hfma2(r, hr, __hneg2(__hmul2(s, hi))), y = __hfma2(r, hi, __hmul2(s, hr));
    o[i] = *(uint32_t*)&x; o[4 + i] = *(uint32_t*)&y;
  }
  sts128(a, o[0], o[1], o[2], o[3]);
  sts128(a + 128, o[4], o[5], o[6], o[7]);
}

template <int S> __device__ __forceinline__ void near_step(float* d, uint64_t ud, const uint32_t* a) {
  constexpr int arr = (S & 1) ? 0 : 2;
  constexpr int slot = (S & 1) ? (S - 1) / 2 : S / 2;
  const uint64_t desc = ud + (uint64_t)((arr * UA_ARR + slot * 16) >> 4);
  if constexpr (S < 16) wgmma_n64(d, a, desc);
  else if constexpr (S < 32) wgmma_n56(d, a, desc);
  else if constexpr (S < 34) wgmma_n48(d, a, desc);
  else if constexpr (S == 63) wgmma_n40(d, a, desc);
  else wgmma_n32(d, a, desc);
}
template <int S0, int NS> __device__ __forceinline__ void near_load(uint32_t (*a)[4], uint32_t wa) {
  a[0][2] = lds32(wa + (uint32_t)((2 * S0 - 1) * 32));
  #pragma unroll
  for (int i = 0; i < NS; i++) {
    a[i][0] = lds32(wa + (2 * (S0 + i)) * 32);
    a[i][1] = lds32(wa + (2 * (S0 + i) + 1) * 32);
  }
  #pragma unroll
  for (int i = 0; i < NS; i++) {
    a[i][3] = rcopy(a[i][0]);
    if (i + 1 < NS) a[i + 1][2] = rcopy(a[i][1]);
  }
}
template <int S0, int NS> __device__ __forceinline__ void near_issue(float* d, uint64_t ua, uint32_t (*a)[4]) {
  wg_fence();
  near_step<S0>(d, ua, a[0]);
  if constexpr (NS > 1) near_step<S0 + 1>(d, ua, a[1]);
  if constexpr (NS > 2) near_step<S0 + 2>(d, ua, a[2]);
  if constexpr (NS > 3) near_step<S0 + 3>(d, ua, a[3]);
  if constexpr (NS > 4) near_step<S0 + 4>(d, ua, a[4]);
  if constexpr (NS > 5) near_step<S0 + 5>(d, ua, a[5]);
  wg_commit();
}

__device__ __forceinline__ void sts2x(uint32_t o, const uint32_t* w) {
  const bool sw = (threadIdx.x >> 2) & 1;
  sts128(o + (sw ? 16 : 0), sw ? w[4] : w[0], sw ? w[5] : w[1], sw ? w[6] : w[2], sw ? w[7] : w[3]);
  sts128(o + (sw ? 0 : 16), sw ? w[0] : w[4], sw ? w[1] : w[5], sw ? w[2] : w[6], sw ? w[3] : w[7]);
}
__device__ __forceinline__ void ytab_chunk(uint32_t ub, uint32_t yb, int chi) {
  auto ca = [&](int c) { return ub + (c & 3) * UA_ARR - (c >> 2) * 16; };
  const uint4 z = lds128(ca(chi - 2)), a = lds128(ca(chi - 1)), b = lds128(ca(chi)), c = lds128(ca(chi + 1));
  const float v[23] = {bf_hi(z.z), bf_lo(z.w), bf_hi(z.w),
                       bf_lo(a.x), bf_hi(a.x), bf_lo(a.y), bf_hi(a.y), bf_lo(a.z), bf_hi(a.z), bf_lo(a.w), bf_hi(a.w),
                       bf_lo(b.x), bf_hi(b.x), bf_lo(b.y), bf_hi(b.y), bf_lo(b.z), bf_hi(b.z), bf_lo(b.w), bf_hi(b.w),
                       bf_lo(c.x), bf_hi(c.x), bf_lo(c.y), bf_hi(c.y)};
  float s[24];
  s[13] = 0.f; s[14] = v[13]; s[12] = -v[12];
  #pragma unroll
  for (int i = 15; i < 24; i++) s[i] = s[i - 1] + v[i - 1];
  #pragma unroll
  for (int i = 11; i >= 0; i--) s[i] = s[i + 1] - v[i];
  uint32_t w[8];
  {
    #pragma unroll
    for (int i = 0; i < 8; i++) w[i] = pack_bf2(s[i + 14] - s[i + 9], s[i + 9] - s[i + 6]);
    const int cp = (chi + ((chi + 4) >> 3)) * 32;
    uint32_t o = yb + Y2_OFF + cp;
    sts2x(o, w);
    if (chi < 128) {
      #pragma unroll
      for (int i = 0; i < 8; i++) w[i] = pack_bf2(s[i + 16] - s[i + 7], s[i + 7] - s[i]);
      o = yb + Y3_OFF + cp;
      sts2x(o, w);
    }
  }
}

__device__ __forceinline__ uint32_t ldv32(uint32_t a) { uint32_t v; asm volatile("ld.volatile.shared.u32 %0, [%1];" : "=r"(v) : "r"(a) : "memory"); return v; }
__device__ __forceinline__ void ld_frag(uint32_t* n, uint32_t x, int dm) { n[0] = ldv32(x); n[1] = ldv32(x + 32); n[2] = ldv32(x + dm); }
__device__ __forceinline__ void far_octet(float (*acc)[4], int j0, uint32_t yb, uint32_t kb, int g, int q, const uint32_t (*b2)[2]) {
  const int mu = g >> 1;
  const uint32_t zr = ldv32(kb);
  uint32_t a[4][4];
  if (j0 >= 4) {
    const uint32_t ya = yb + Y2_OFF + (72 * (j0 - 8) + 48 - 16 * q + (q < 2 ? 8 : 0) + g) * 4;
    const int dm = (q == 1) ? -64 : -32;
    #pragma unroll
    for (int i = 0; i < 3; i++) ld_frag(a[i], ya + (3 - i) * 288, dm);
    #pragma unroll
    for (int i = 0; i < 12; i++) {
      const int br = 3 - i;
      if ((i & 3) == 1 && j0 + br < 7) break;
      if (i + 3 < 12) ld_frag(a[(i + 3) & 3], ya + (br - 3) * 288, dm);
      uint32_t* c = a[i & 3];
      c[3] = c[0] + zr;
      #pragma unroll
      for (int j = 0; j < 4; j++) { const int s = j - br; if (s >= 0 && s < 9) mma_bf16(acc[j], c[0], c[1], c[2], c[3], b2[s]); }
    }
  }
  if (j0 >= 12) {
    const uint32_t ya = yb + Y3_OFF + (72 * (j0 - 16) + 48 - 16 * q + (q < 2 ? 8 : 0) + g) * 4;
    #pragma unroll
    for (int i = 0; i < 3; i++) { a[i][0] = ldv32(ya + (3 - i) * 288); a[i][1] = ldv32(ya + (3 - i) * 288 + 32); }
    uint32_t b3[9][2];
    #pragma unroll
    for (int s = 0; s < 9; s++) { b3[s][0] = ldv32(kb + (TW_3 + mu + q + 8 * s) * 4); b3[s][1] = ldv32(kb + (TW_3 + mu + q + 8 * s + 4) * 4); }
    #pragma unroll
    for (int i = 0; i < 17; i++) {
      const int br = 3 - i;
      if ((i & 3) == 1 && j0 + br < 15) break;
      if (i + 3 < 18) { uint32_t* n = a[(i + 3) & 3]; n[0] = ldv32(ya + (br - 3) * 288); n[1] = ldv32(ya + (br - 3) * 288 + 32); }
      uint32_t* c = a[i & 3];
      c[2] = a[(i + 1) & 3][0] + zr; c[3] = a[(i + 1) & 3][1] + zr;
      #pragma unroll
      for (int j = 0; j < 4; j++) { const int s2 = j - br; if (s2 >= 0 && !(s2 & 1)) mma_bf16(acc[j], c[0], c[1], c[2], c[3], b3[s2 >> 1]); }
    }
  }
}

__global__ void __cluster_dims__(2, 1, 1) __launch_bounds__(NTHR, 1)
ssm_gated_kernel(const __grid_constant__ CUtensorMap tmap_u, const __grid_constant__ Params P) {
  extern __shared__ __align__(1024) unsigned char smem[];
  const uint32_t sb = smem_u32(smem);
  const int tid = threadIdx.x, warp = __shfl_sync(~0u, tid >> 5, 0), lane = tid & 31;
  const int g = lane >> 2, q = lane & 3;
  const int cta = blockIdx.x, c0 = cta * 4, rank = cta & 1;
  const uint32_t mb = sb + SM_BAR;
  if (tid == 0) {
    mbar_init(mb + MB_PRM, 1); mbar_init(mb + MB_ROW, 1);
    fence_async();
    mbar_expect(mb + MB_PRM, 10240 + 64);
    #pragma unroll
    for (int i = 0; i < 10; i++) bulk_g2s(sb + SM_PRM + i * 1024, P.pm[i] + c0 * NMODE, 1024, mb + MB_PRM);
    #pragma unroll
    for (int i = 0; i < 4; i++) bulk_g2s(sb + SM_PRM + 10240 + i * 16, P.pv[i] + (cta >> 1) * 8, 16, mb + MB_PRM);
    mbar_expect(mb + MB_ROW, 16384 + 1024);
    bulk_g2s(sb + SM_ROW, P.u + (size_t)cta * 16 * DIM, 16384, mb + MB_ROW);
    bulk_g2s(sb + SM_ROW + 16384, P.gate_w, 1024, mb + MB_ROW);
  }
  if (tid == 32) {
    mbar_init(mb + MB_U, 1); mbar_init(mb + MB_URDY, 1);
    mbar_init(mb + MB_G1, 8); mbar_init(mb + MB_G23, 8); mbar_init(mb + MB_PEER, 1); mbar_init(mb + MB_GW, 4);
    #pragma unroll
    for (int i = 0; i < 4; i++) mbar_init(mb + MB_Y + 8 * i, 8);
    #pragma unroll
    for (int i = 0; i < 8; i++) { mbar_init(mb + MB_LOC + 8 * i, 20); mbar_init(mb + MB_RX + 8 * i, 1); }
    asm volatile("fence.mbarrier_init.release.cluster;" ::: "memory");
    fence_async();
  }
  STAMP(0);

  if (warp < 16) {
    const int ch = warp >> 2, br = (warp >> 1) & 1, w0 = warp & 1;
    asm volatile("setmaxnreg.inc.sync.aligned.u32 96;");
    for (int i = tid; i < (SM_Y01 - SM_UA) / 16; i += 512) sts128(sb + SM_UA + i * 16, 0, 0, 0, 0);
    asm volatile("barrier.cluster.arrive.relaxed.aligned;" ::: "memory");
    bar_sync(0, NTHR);
    const uint32_t tab = sb + SM_TAB + (ch * 2 + br) * TAB_SZ;
    const uint32_t yb = sb + (ch < 2 ? SM_Y01 + ch * Y_CH : SM_Y23 + (ch - 2) * 8 * GSLOT);
    {
      const uint32_t gb = sb + SM_G + ch * (8 * GSLOT) + (w0 * 4 + (lane >> 3)) * GSLOT + (lane & 7) * 16;
      const uint64_t gd = mkdesc(sb + SM_G + ch * (8 * GSLOT), 128, 256);
      float a2[2], th[2]; cf cc[2];
      const uint32_t pp = sb + SM_PRM + br * 4096 + ch * 256 + (w0 * 32 + lane) * 2;
      const uint32_t pl = sb + SM_PRM + 10240 + br * 16 + rank * 8 + ch * 2;
      mbar_wait(mb + MB_PRM);
      STAMP(1);
      const float dt = bf16_round(exp_acc(ldsbf(pl)));
      float mxf = 0.f;
      #pragma unroll
      for (int r = 0; r < 2; r++) {
        float are = ldsbf(pp + r * 128);
        if (br) are = -bf16_round(exp_acc(are));
        a2[r] = (are * dt) * 1.4426950408889634f; th[r] = ldsbf(pp + r * 128 + 1024) * dt;
        cf c = {ldsbf(pp + r * 128 + 2048), ldsbf(pp + r * 128 + 3072)}, dB = {dt + dt, 0.f};
        if (!br) { dB.x = dt * ldsbf(pp + r * 128 + 8192); dB.y = dt * ldsbf(pp + r * 128 + 9216); }
        c = cmul(c, dB); cc[r].x = c.x; cc[r].y = -c.y;
        mxf = fmaxf(mxf, fmaxf(fabsf(c.x), fabsf(c.y)));
      }
      const uint32_t mx = __reduce_max_sync(~0u, __float_as_uint(mxf));
      if (lane == 0) sts32(sb + SM_MX + warp * 4, mx);
      bar_sync(1 + ch, 128);
      const int e = min(max((int)(max(mx, lds32(sb + SM_MX + (warp ^ 1) * 4)) >> 23), 1), 252);
      const float sc = __uint_as_float((uint32_t)(253 - e) << 23);
      float d[24];
      #pragma unroll
      for (int i = 0; i < 24; i++) d[i] = 0.f;
      #pragma unroll 1
      for (int r = 0; r < 2; r++) {
        const float al = r ? a2[1] : a2[0], tt = r ? th[1] : th[0];
        cf c = r ? cc[1] : cc[0]; c.x *= sc; c.y *= sc;
        const cf w1 = cexp_fast(al, tt, 1.f), w64 = cexp_fast(al, tt, 64.f);
        const cf w2 = csq(w1), w4 = csq(w2), w8 = csq(w4), w16 = csq(w8), w32 = csq(w16);
        const cf w128 = csq(w64), w256 = csq(w128), w512 = csq(w256), w1024 = csq(w512);
        const uint32_t ab = gb + br * 1024, bb = gb + 2048 + br * 768;
        const cf c1 = cmulc(c, w1), c512 = cmulc(c, w512), c768 = cmulc(c512, w256);
        hp t0, t1, t2, t3, m;
        t0.r = pack_h2(c.x, c1.x); t0.i = pack_h2(c.y, c1.y);
        t1 = hmul<true>(t0, hbro(w2)); m = hbro(w4); t2 = hmul<true>(t0, m); t3 = hmul<true>(t1, m);
        if (!r && ch) bar_sync(4 + ch, 256);
        if (r) bar_sync(1 + ch, 128);
        put4(bb, t0, t1, t2, t3);
        hp z; z.r = pack_h2(c512.x, c768.x); z.i = pack_h2(c512.y, c768.y);
        const hp z4 = hmul<true>(z, m);
        m = hbro(w256);
        hp u0, u1; u0.r = __byte_perm(z.r, z4.r, 0x5410); u0.i = __byte_perm(z.i, z4.i, 0x5410);
        u1.r = __byte_perm(z.r, z4.r, 0x7632); u1.i = __byte_perm(z.i, z4.i, 0x7632);
        put4(bb + 256, hmul<true>(hlo(t0, t1), m), hmul<true>(hlo(t2, t3), m), u0, u1);
        m = hbro(w1024);
        u0 = hmul<true>(z, hbro(w512)); u1 = hmul<true>(z, m);
        const hp u2 = hmul<true>(u0, m);
        put4(bb + 512, u0, u1, u2, u2);
        t0.r = pack_h2(1.f, w8.x); t0.i = pack_h2(0.f, w8.y);
        t1 = hmul<false>(t0, hbro(w16)); m = hbro(w32); t2 = hmul<false>(t0, m); t3 = hmul<false>(t1, m);
        put4(ab, t0, t1, t2, t3);
        m = hbro(w64);  put4(ab + 256, hmul<false>(t0, m), hmul<false>(t1, m), hmul<false>(t2, m), hmul<false>(t3, m));
        m = hbro(w128); put4(ab + 512, hmul<false>(t0, m), hmul<false>(t1, m), hmul<false>(t2, m), hmul<false>(t3, m));
        m = hbro(cmul(w128, w64)); put4(ab + 768, hmul<false>(t0, m), hmul<false>(t1, m), hmul<false>(t2, m), hmul<false>(t3, m));
        if (!r && ch < 3) bar_arrive(5 + ch, 256);
        fence_async();
        bar_sync(1 + ch, 128);
        STAMP(2 + r);
        fence_acc<24>(d);
        wg_fence();
        #pragma unroll
        for (int ks = 0; ks < 8; ks++) wgmma_ss48(d, gd + (uint64_t)(ks * GSLOT >> 4), gd + (uint64_t)((ks * GSLOT + 2048) >> 4));
        wg_commit();
        wg_wait<0>();
        fence_acc<24>(d);
      }
      const float isc = __uint_as_float((uint32_t)(e + 1) << 23);
      const int jr = w0 * 16 + g;
      const uint32_t a0 = tab + (TW_W + 8 * jr + 2 * q) * 4;
      const uint32_t a1 = tab + (q < 2 ? TW_W + 256 + 8 * jr + 4 * q : TW_2 + 6 + 32 * (q - 2) + jr) * 4;
      const uint32_t a3 = tab + TW_3 * 4 + (6 + 64 * q + jr) * 2;
      if (lane == 0) mbar_arrive(mb + (ch < 2 ? MB_G1 : MB_G23));
      float k[12];
      #pragma unroll
      for (int i = 0; i < 12; i++) k[i] = (br ? d[12 + i] : d[i]) * isc;
      if (jr == 0 && q == 0) k[0] += ldsbf(pl + 32);
      #pragma unroll
      for (int h = 0; h < 2; h++) {
        uint32_t w = pack_bf2(k[2 * h + 1], k[2 * h]);
        sts16(a0 + h * 256, w >> 16); sts32(a0 + h * 256 + 4, w); sts16(a0 + h * 256 + 10, w);
        w = pack_bf2(k[4 + 2 * h], k[5 + 2 * h]);
        if (q < 2) {
          const uint32_t a = a1 + h * 256, w0w = __byte_perm(w, w, 0x1010);
          if (h == 0 && jr == 0 && q == 0) sts16(a, w0w); else { sts16(a - 4, w0w); sts32(a, w0w); }
          sts32(a + 4, w0w); sts32(a + 8, __byte_perm(w, w, 0x1032)); sts16(a + 14, w >> 16);
        } else sts32(a1 + h * 32, w);
        w = pack_bf2(k[8 + 2 * h], k[9 + 2 * h]);
        if (q < 2 || (q == 2 && h == 0 && jr == 0)) sts16(a3 + h * 16, w);
        if (q < 2) sts16(a3 + h * 16 + 64, w >> 16);
        if (h == 0 && jr == 0 && q == 0) { sts16(tab + (TW_X + 1019 - 976) * 4, w); sts16(tab + (TW_X + 1020 - 976) * 4 + 2, w); }
      }
      bar_sync(1 + ch, 128);
      if (w0 == 1 && g == 7 && (q & 1)) {
        const uint32_t w = pack_bf2(k[7] - ldsbf(tab + (q == 3 ? TW_3 * 4 + 12 : TW_2 * 4 + 24)), 0.f);
        if (q == 3) sts16(a1 + 32 + 2, w); else { sts16(a1 + 256 + 8, w); sts16(a1 + 256 + 14, w); }
      }
      STAMP(4);
    }
    {
      const uint64_t ua = mkdesc(sb + SM_UA + ch * UA_CH, UA_ARR, 128);
      const uint32_t wa = tab + (TW_W + 16 * w0 + g - 2 * q - 16) * 4;
      float d[32];
      #pragma unroll
      for (int i = 0; i < 32; i++) d[i] = 0.f;
      uint32_t A[4][4], B[4][4];
      near_load<0, 4>(A, wa);
      near_load<4, 4>(B, wa);
      STAMP(6);
      mbar_wait(mb + MB_URDY);
      STAMP(7);
      fence_acc<32>(d);
      near_issue<0, 4>(d, ua, A);
      near_issue<4, 4>(d, ua, B);   wg_wait<1>();
      near_load<8, 4>(A, wa);   near_issue<8, 4>(d, ua, A);   wg_wait<1>();
      near_load<12, 4>(B, wa);  near_issue<12, 4>(d, ua, B);  wg_wait<1>();
      near_load<16, 4>(A, wa);  near_issue<16, 4>(d, ua, A);  wg_wait<1>();
      near_load<20, 4>(B, wa);  near_issue<20, 4>(d, ua, B);  wg_wait<1>();
      near_load<24, 4>(A, wa);  near_issue<24, 4>(d, ua, A);  wg_wait<1>();
      bar_sync(1 + ch, 128);
      near_load<28, 4>(B, wa);  near_issue<28, 4>(d, ua, B);  wg_wait<1>();
      near_load<32, 2>(A, wa);  near_issue<32, 2>(d, ua, A);  wg_wait<1>();
      near_load<63, 3>(B, wa - (uint32_t)((976 + TW_W - TW_X) * 4));
      near_issue<63, 1>(d, ua, B);
      near_issue<64, 2>(d, ua, B + 1);
      mbar_wait(mb + MB_GW);
      mbar_wait(mb + MB_G1);
      wg_wait<0>();
      fence_acc<32>(d);
      STAMP(8);
      const int m = lane >> 3, tl = 7 - (lane & 7);
      const uint32_t ga = sb + SM_GW + br * 5120 + ((3 - q) * 40 + 16 * w0 + g) * 4;
      const int c16 = 4 * (tl & 3) + 2 * w0 + (m & 1);
      const uint32_t ta = sb + SM_T + (m >> 1) * 4096 + (tl >> 2) * 2048 + (br * 4 + ch) * 256 + ((c16 ^ (tl >> 1) ^ (rank * 4 + ch)) * 16);
      #pragma unroll
      for (int i = 0; i < 8; i += 2) {
        uint32_t r[4];
        #pragma unroll
        for (int kk = 0; kk < 4; kk++) {
          const int ii = i + (kk >> 1), h = kk & 1;
          const uint32_t gw = lds32(ga + (ii * 160 + 8 * h) * 4);
          r[kk] = pack_bf2(d[4 * (7 - ii) + 2 * h] * bf_lo(gw), d[4 * (7 - ii) + 2 * h + 1] * bf_hi(gw));
        }
        stsm4t(ta + i * 4096, r);
      }
      __syncwarp();
      if (lane < 8) mbar_arrive(mb + MB_LOC + 8 * lane);
    }
    STAMP(9);
    {
      const uint32_t kb = sb + SM_TAB + (ch * 2 + (g & 1)) * TAB_SZ;
      uint32_t b2[9][2];
      #pragma unroll
      for (int s = 0; s < 9; s++)
        asm volatile("ld.shared.v2.u32 {%0,%1}, [%2];" : "=r"(b2[s][0]), "=r"(b2[s][1]) : "r"(kb + (TW_2 + 2 * (g >> 1) + 2 * q + 8 * s) * 4) : "memory");
      mbar_wait(mb + MB_Y + 8 * ch);
      STAMP(10);
      const int c32 = lane, c16 = c32 & 15;
      const uint32_t t3a = sb + SM_T3 + (c32 >> 4) * 1024 + ch * 256 + ((c16 ^ (c32 >> 3) ^ (rank * 4 + ch)) * 16);
      #pragma unroll 1
      for (int ps = 0; ps < 2; ps++) {
        const int o4 = (warp + ch) & 3, oc = ps ? 7 - o4 : o4, j0 = 4 * oc;
        float acc[4][4];
        uint32_t gq[4];
        #pragma unroll
        for (int j = 0; j < 4; j++) {
          gq[j] = lds32(sb + SM_GE + (32 * (j0 + j) + 8 * q + g) * 4);
          acc[j][0] = acc[j][1] = acc[j][2] = acc[j][3] = 0.f;
        }
        far_octet(acc, j0, yb, kb, g, q, b2);
        uint32_t r[4];
        #pragma unroll
        for (int j = 0; j < 4; j++)
          r[j] = pack_bf2(fmaf(bf_lo(gq[j]), acc[j][0] - acc[j][1], acc[j][1]), fmaf(bf_hi(gq[j]), acc[j][2] - acc[j][3], acc[j][3]));
        stsm4t(t3a + oc * 2048, r);
        warp_arrive(mb + MB_LOC + 8 * oc, lane);
        STAMP(11 + ps);
      }
    }
  } else {
    asm volatile("setmaxnreg.dec.sync.aligned.u32 48;");
    const int aw = warp - 16, at = tid - 512;
    const uint32_t epoch = __ldcg(&g_epoch[cta]) + 1u, tag = epoch & 0xffffu;
    asm volatile("barrier.cluster.arrive.relaxed.aligned;" ::: "memory");
    bar_sync(0, NTHR);
    STAMP(1);
    if (aw >= 4) {
      const int bw = aw - 4, bt = at - 128;
      if (bt == 0) {
        mbar_expect(mb + MB_U, 16384);
        #pragma unroll
        for (int i = 0; i < 4; i++)
          asm volatile("cp.async.bulk.tensor.2d.shared::cluster.global.mbarrier::complete_tx::bytes [%0], [%1, {%3, %4}], [%2];"
                       :: "r"(sb + SM_RAW + i * 4096), "l"((uint64_t)&tmap_u), "r"(mb + MB_U), "r"((cta >> 1) * 8), "r"(rank * 1024 + i * 256) : "memory");
        mbar_expect(mb + MB_PEER, 8192);
        #pragma unroll
        for (int i = 0; i < 8; i++) mbar_expect(mb + MB_RX + 8 * i, 1024);
      }
      mbar_wait(mb + MB_U);
      STAMP(2);
      const int chs = (lane & 7) - rank * 4, m = lane >> 3;
      const uint32_t base = ((unsigned)chs < 4u) ? sb + SM_UA + chs * UA_CH + m * UA_ARR + (63 - rank * 32) * 16
                                                 : sb + SM_XS + 64 + (chs & 3) * XS_CH + m * 512 + 31 * 16;
      #pragma unroll
      for (int hh = 0; hh < 2; hh++) {
        uint32_t r[4][4];
        #pragma unroll
        for (int it = 0; it < 4; it++) ldsm4t(sb + SM_RAW + ((bw * 8 + hh * 4 + it) * 32 + lane) * 16, r[it]);
        #pragma unroll
        for (int it = 0; it < 4; it++) stsm4(base - (bw * 8 + hh * 4 + it) * 16, r[it]);
      }
      fence_async();
      asm volatile("barrier.cluster.wait.aligned;" ::: "memory");
      bar_sync(11, 128);
      if (lane < 4) {
        dsmem_copy(mapa(sb + SM_UA + bw * UA_CH + lane * UA_ARR + (32 - rank * 32) * 16, rank ^ 1),
                   sb + SM_XS + 64 + bw * XS_CH + lane * 512, 512, mapa(mb + MB_PEER, rank ^ 1));
      }
      STAMP(3);
      mbar_wait(mb + MB_PEER);
      if (bt == 0) mbar_arrive(mb + MB_URDY);
      STAMP(4);
    } else {
      mbar_wait(mb + MB_ROW);
      {
        const uint4 gw0 = lds128(sb + SM_ROW + 16384 + lane * 16), gw1 = lds128(sb + SM_ROW + 16384 + 512 + lane * 16);
        float s[4];
        #pragma unroll
        for (int r = 0; r < 4; r++) {
          const uint4 x0 = lds128(sb + SM_ROW + (aw * 4 + r) * 1024 + lane * 16), x1 = lds128(sb + SM_ROW + (aw * 4 + r) * 1024 + 512 + lane * 16);
          const uint32_t xv[8] = {x0.x, x0.y, x0.z, x0.w, x1.x, x1.y, x1.z, x1.w}, wv[8] = {gw0.x, gw0.y, gw0.z, gw0.w, gw1.x, gw1.y, gw1.z, gw1.w};
          float a = 0.f, b = 0.f;
          #pragma unroll
          for (int i = 0; i < 8; i++) {
            __nv_bfloat162 pr2 = __hmul2(*(const __nv_bfloat162*)&xv[i], *(const __nv_bfloat162*)&wv[i]);
            const uint32_t pv = *(uint32_t*)&pr2;
            a += bf_lo(pv); b += bf_hi(pv);
          }
          s[r] = a + b;
        }
        float t0 = (lane & 1) ? s[1] : s[0], t1 = (lane & 1) ? s[3] : s[2];
        t0 += __shfl_xor_sync(~0u, (lane & 1) ? s[0] : s[1], 1); t1 += __shfl_xor_sync(~0u, (lane & 1) ? s[2] : s[3], 1);
        float t = (lane & 2) ? t1 : t0;
        t += __shfl_xor_sync(~0u, (lane & 2) ? t0 : t1, 2);
        #pragma unroll
        for (int o = 4; o < 32; o <<= 1) t += __shfl_xor_sync(~0u, t, o);
        if (lane < 4) {
          const float gv = __fdividef(1.f, 1.f + exp_acc(-bf16_round(t)));
          const uint32_t w = (pack_bf2(gv, gv) & 0xffffu) | (tag << 16);
          asm volatile("st.relaxed.gpu.global.u32 [%0], %1;" :: "l"(&g_gate[cta * 16 + aw * 4 + lane]), "r"(w) : "memory");
        }
      }
      STAMP(2);
      asm volatile("barrier.cluster.wait.aligned;" ::: "memory");
      mbar_wait(mb + MB_URDY);
      if (at == 0) __stcg(&g_epoch[cta], epoch);
      #pragma unroll 1
      for (int kk = 0; kk < 2; kk++) {
        uint32_t x[4], y[4]; int it = 0; bool ok;
        do {
          ok = true;
          #pragma unroll
          for (int k = 0; k < 4; k++) {
            const uint32_t* gp = &g_gate[64 * (aw + 4 * k + 16 * kk) + lane];
            asm volatile("ld.relaxed.gpu.global.u32 %0, [%1];" : "=r"(x[k]) : "l"(gp) : "memory");
            asm volatile("ld.relaxed.gpu.global.u32 %0, [%1];" : "=r"(y[k]) : "l"(gp + 32) : "memory");
          }
          #pragma unroll
          for (int k = 0; k < 4; k++) ok = ok && (x[k] >> 16) == tag && (y[k] >> 16) == tag;
        } while (!ok && ++it < (1 << 18));
        #pragma unroll
        for (int k = 0; k < 4; k++) {
          uint32_t a = sb + SM_GW + ((aw + 4 * k + 16 * kk) * 40 + lane) * 4;
          sts32(a, __byte_perm(y[k], x[k], 0x5410));
          sts32(a + 5120, pack_bf2(1.f - bf_lo(y[k]), 1.f - bf_lo(x[k])));
          const uint32_t ge = sb + SM_GE + ((aw + 4 * k + 16 * kk) * 32 + (lane >> 4) * 8 + (lane & 7)) * 4 + ((lane >> 3) & 1) * 2;
          sts16(ge, x[k]); sts16(ge + 64, y[k]);
        }
      }
      warp_arrive(mb + MB_GW, lane);
      STAMP(4);
    }
    bar_sync(12, 256);
    #pragma unroll 1
    for (int c = 0; c < 4; c++) {
      const uint32_t yb = sb + (c < 2 ? SM_Y01 + c * Y_CH : SM_Y23 + (c - 2) * 8 * GSLOT);
      if (c == 0) mbar_wait(mb + MB_G23);
      if (at >= 204) {
        const int i = at - 204;
        sts128(yb + (i < 18 ? i * 16 : Y3_OFF - 576 + (i - 18) * 16), 0, 0, 0, 0);
      }
      if (at < 193) ytab_chunk(sb + SM_UA + c * UA_CH + 63 * 16, yb, at - 1);
      warp_arrive(mb + MB_Y + 8 * c, lane);
      STAMP(5 + c);
    }
    {
      const int k = aw;
      const uint32_t tk = sb + SM_T + k * 4096 + lane * 16, t3 = sb + SM_T3 + k * 2048 + lane * 16;
      mbar_wait(mb + MB_LOC + 8 * k);
      STAMP(11);
      #pragma unroll
      for (int i = 0; i < 4; i++) {
        const int hf = (i >> 1) ^ rank ^ 1, o = (i & 1) * 512;
        const uint4 a = lds128(tk + hf * 2048 + o), b = lds128(tk + hf * 2048 + 1024 + o), c = lds128(t3 + hf * 1024 + o);
        sts128(t3 + hf * 1024 + o, hadd(hadd(a.x, b.x), c.x), hadd(hadd(a.y, b.y), c.y), hadd(hadd(a.z, b.z), c.z), hadd(hadd(a.w, b.w), c.w));
        if (i == 1) {
          fence_async();
          __syncwarp();
          if (lane == 0) dsmem_copy(mapa(sb + SM_RX + k * 1024, rank ^ 1), sb + SM_T3 + k * 2048 + (rank ^ 1) * 1024, 1024, mapa(mb + MB_RX + 8 * k, rank ^ 1));
        }
      }
      __syncwarp();
      mbar_wait(mb + MB_RX + 8 * k);
      STAMP(12);
      const int m = lane >> 3, j = lane & 7;
      const uint32_t src = (((j >> 2) == rank) ? sb + SM_T3 + k * 2048 + rank * 1024 : sb + SM_RX + k * 1024) + (j & 3) * 256;
      __nv_bfloat16* op = P.out + (size_t)(k * 256 + rank * 128 + g) * DIM + (cta >> 1) * 8 + 2 * q;
      #pragma unroll
      for (int it = 0; it < 4; it++) {
        const int c16 = 4 * it + m;
        uint32_t r[4];
        ldsm4t(src + ((c16 ^ (rank * 2 + (c16 >> 3)) ^ j) * 16), r);
        #pragma unroll
        for (int i = 0; i < 4; i++) {
          *(uint32_t*)(op + (size_t)(it * 32 + i * 8) * DIM) = r[i];
        }
      }
      STAMP(13);
    }
    asm volatile("barrier.cluster.arrive.relaxed.aligned;" ::: "memory");
    asm volatile("barrier.cluster.wait.aligned;" ::: "memory");
    STAMP(14);
    STAMP_DUMP();
  }
}

typedef CUresult (*EncodeFn)(CUtensorMap*, CUtensorMapDataType, cuuint32_t, void*, const cuuint64_t*, const cuuint64_t*,
                             const cuuint32_t*, const cuuint32_t*, CUtensorMapInterleave, CUtensorMapSwizzle,
                             CUtensorMapL2promotion, CUtensorMapFloatOOBfill);
}

extern "C" void kernel_launch(void* const* d_in, const int* in_sizes, int n_in, void* d_out, int out_size) {
  (void)in_sizes; (void)n_in; (void)out_size;
  static EncodeFn enc = nullptr;
  if (!enc) {
    void* fn = nullptr; cudaDriverEntryPointQueryResult qr;
    cudaGetDriverEntryPoint("cuTensorMapEncodeTiled", &fn, cudaEnableDefault, &qr);
    enc = (EncodeFn)fn;
    cudaFuncSetAttribute(ssm_gated_kernel, cudaFuncAttributeMaxDynamicSharedMemorySize, SM_TOTAL + STAMP_EXTRA);
  }
  CUtensorMap tm;
  cuuint64_t gd[2] = {(cuuint64_t)DIM, (cuuint64_t)SEQ}; cuuint64_t gs[1] = {(cuuint64_t)DIM * 2};
  cuuint32_t bd[2] = {8, 256}; cuuint32_t es[2] = {1, 1};
  enc(&tm, CU_TENSOR_MAP_DATA_TYPE_BFLOAT16, 2, d_in[0], gd, gs, bd, es, CU_TENSOR_MAP_INTERLEAVE_NONE,
      CU_TENSOR_MAP_SWIZZLE_NONE, CU_TENSOR_MAP_L2_PROMOTION_L2_128B, CU_TENSOR_MAP_FLOAT_OOB_FILL_NONE);
  Params P;
  typedef const __nv_bfloat16* bp;
  P.u = (bp)d_in[0];
  const int mi[10] = {1, 2, 5, 6, 10, 11, 12, 13, 3, 4}, vi[4] = {7, 14, 8, 15};
  for (int i = 0; i < 10; i++) P.pm[i] = (bp)d_in[mi[i]];
  for (int i = 0; i < 4; i++) P.pv[i] = (bp)d_in[vi[i]];
  P.gate_w = (bp)d_in[16];
  P.out = (__nv_bfloat16*)d_out;
  ssm_gated_kernel<<<NCTA, NTHR, SM_TOTAL + STAMP_EXTRA, cudaStreamPerThread>>>(tm, P);
}
```

```cpp
#include <cuda_runtime.h>
#include <cuda_bf16.h>
#include <cuda_fp16.h>
#include <cuda.h>
#include <stdint.h>

#define STAMP(i) __syncwarp()
#define STAMP_EXTRA 0
#define STAMP_DUMP() do {} while (0)

namespace {

constexpr int SEQ = 2048, DIM = 512, NMODE = 128;
constexpr int NCTA = 128, NTHR = 768;

constexpr int GSLOT   = 3584;
constexpr int GBUF    = 16 * GSLOT;
constexpr int Y2_OFF = 128 * 4, Y3_OFF = (128 + 1536 + 128) * 4, Y_CH = (128 + 1536 + 128 + 1024) * 4;
constexpr int SM_G    = 0;
constexpr int SM_T    = 0;
constexpr int SM_T3   = SM_T + 32768;
constexpr int SM_RX   = SM_T3 + 16384;
constexpr int SM_Y23  = 16 * GSLOT + 1024;
constexpr int SM_RAW  = 2 * GBUF;
constexpr int SM_GW   = SM_RAW, SM_GE = SM_RAW + 10240;
constexpr int XS_CH   = 4 * 512 + 16;
constexpr int SM_XS   = SM_RAW + 16384;
constexpr int UA_ARR  = 74 * 16;
constexpr int UA_CH   = 4 * UA_ARR + 16;
constexpr int SM_UA   = SM_XS + 8320;
constexpr int TW_W = 32, TW_X = 576, TW_2 = 656, TW_3 = 736, TW_TOT = 816;
constexpr int TAB_SZ  = TW_TOT * 4;
constexpr int SM_TAB  = SM_UA + 4 * UA_CH;
constexpr int SM_Y01  = SM_TAB + 8 * TAB_SZ;
constexpr int SM_ROW  = SM_Y01;
constexpr int SM_PRM  = SM_Y01 + 2 * Y_CH;
constexpr int SM_MX   = SM_PRM + 10240 + 64;
constexpr int SM_BAR  = SM_MX + 128;
constexpr int SM_TOTAL = SM_BAR + 256;
constexpr int MB_PRM = 0, MB_U = 8, MB_PEER = 16, MB_URDY = 24, MB_ROW = 32, MB_G1 = 40, MB_GW = 48, MB_G23 = 56, MB_Y = 64  , MB_LOC = 96, MB_RX = 160;
static_assert(SM_TOTAL + STAMP_EXTRA <= 232448, "smem");
static_assert(1024 + Y_CH <= 8 * GSLOT && SM_RX + 8192 <= GBUF, "alias");
static_assert(SM_UA % 128 == 0 && SM_XS % 128 == 0 && SM_TAB % 16 == 0 && SM_Y01 % 16 == 0 && Y_CH % 16 == 0 && SM_T % 128 == 0, "align");

__device__ uint32_t g_gate[SEQ];
__device__ uint32_t g_epoch[NCTA];

struct Params {
  const __nv_bfloat16* u;
  const __nv_bfloat16* pm[10];
  const __nv_bfloat16* pv[4];
  const __nv_bfloat16* gate_w;
  __nv_bfloat16* out;
};

__device__ __forceinline__ void wgmma_n32(float* d, const uint32_t* a, uint64_t desc) {
  asm volatile("wgmma.mma_async.sync.aligned.m64n32k16.f32.bf16.bf16 {%0, %1, %2, %3, %4, %5, %6, %7, %8, %9, %10, %11, %12, %13, %14, %15}, {%16, %17, %18, %19}, %20, 1, 1, 1, 0;\n"
    : "+f"(d[0]), "+f"(d[1]), "+f"(d[2]), "+f"(d[3]), "+f"(d[4]), "+f"(d[5]), "+f"(d[6]), "+f"(d[7]), "+f"(d[8]), "+f"(d[9]), "+f"(d[10]), "+f"(d[11]), "+f"(d[12]), "+f"(d[13]), "+f"(d[14]), "+f"(d[15])
    : "r"(a[0]), "r"(a[1]), "r"(a[2]), "r"(a[3]), "l"(desc));
}

__device__ __forceinline__ void wgmma_n40(float* d, const uint32_t* a, uint64_t desc) {
  asm volatile("wgmma.mma_async.sync.aligned.m64n40k16.f32.bf16.bf16 {%0, %1, %2, %3, %4, %5, %6, %7, %8, %9, %10, %11, %12, %13, %14, %15, %16, %17, %18, %19}, {%20, %21, %22, %23}, %24, 1, 1, 1, 0;\n"
    : "+f"(d[0]), "+f"(d[1]), "+f"(d[2]), "+f"(d[3]), "+f"(d[4]), "+f"(d[5]), "+f"(d[6]), "+f"(d[7]), "+f"(d[8]), "+f"(d[9]), "+f"(d[10]), "+f"(d[11]), "+f"(d[12]), "+f"(d[13]), "+f"(d[14]), "+f"(d[15]), "+f"(d[16]), "+f"(d[17]), "+f"(d[18]), "+f"(d[19])
    : "r"(a[0]), "r"(a[1]), "r"(a[2]), "r"(a[3]), "l"(desc));
}

__device__ __forceinline__ void wgmma_n48(float* d, const uint32_t* a, uint64_t desc) {
  asm volatile("wgmma.mma_async.sync.aligned.m64n48k16.f32.bf16.bf16 {%0, %1, %2, %3, %4, %5, %6, %7, %8, %9, %10, %11, %12, %13, %14, %15, %16, %17, %18, %19, %20, %21, %22, %23}, {%24, %25, %26, %27}, %28, 1, 1, 1, 0;\n"
    : "+f"(d[0]), "+f"(d[1]), "+f"(d[2]), "+f"(d[3]), "+f"(d[4]), "+f"(d[5]), "+f"(d[6]), "+f"(d[7]), "+f"(d[8]), "+f"(d[9]), "+f"(d[10]), "+f"(d[11]), "+f"(d[12]), "+f"(d[13]), "+f"(d[14]), "+f"(d[15]), "+f"(d[16]), "+f"(d[17]), "+f"(d[18]), "+f"(d[19]), "+f"(d[20]), "+f"(d[21]), "+f"(d[22]), "+f"(d[23])
    : "r"(a[0]), "r"(a[1]), "r"(a[2]), "r"(a[3]), "l"(desc));
}

__device__ __forceinline__ void wgmma_n56(float* d, const uint32_t* a, uint64_t desc) {
  asm volatile("wgmma.mma_async.sync.aligned.m64n56k16.f32.bf16.bf16 {%0, %1, %2, %3, %4, %5, %6, %7, %8, %9, %10, %11, %12, %13, %14, %15, %16, %17, %18, %19, %20, %21, %22, %23, %24, %25, %26, %27}, {%28, %29, %30, %31}, %32, 1, 1, 1, 0;\n"
    : "+f"(d[0]), "+f"(d[1]), "+f"(d[2]), "+f"(d[3]), "+f"(d[4]), "+f"(d[5]), "+f"(d[6]), "+f"(d[7]), "+f"(d[8]), "+f"(d[9]), "+f"(d[10]), "+f"(d[11]), "+f"(d[12]), "+f"(d[13]), "+f"(d[14]), "+f"(d[15]), "+f"(d[16]), "+f"(d[17]), "+f"(d[18]), "+f"(d[19]), "+f"(d[20]), "+f"(d[21]), "+f"(d[22]), "+f"(d[23]), "+f"(d[24]), "+f"(d[25]), "+f"(d[26]), "+f"(d[27])
    : "r"(a[0]), "r"(a[1]), "r"(a[2]), "r"(a[3]), "l"(desc));
}

__device__ __forceinline__ void wgmma_n64(float* d, const uint32_t* a, uint64_t desc) {
  asm volatile("wgmma.mma_async.sync.aligned.m64n64k16.f32.bf16.bf16 {%0, %1, %2, %3, %4, %5, %6, %7, %8, %9, %10, %11, %12, %13, %14, %15, %16, %17, %18, %19, %20, %21, %22, %23, %24, %25, %26, %27, %28, %29, %30, %31}, {%32, %33, %34, %35}, %36, 1, 1, 1, 0;\n"
    : "+f"(d[0]), "+f"(d[1]), "+f"(d[2]), "+f"(d[3]), "+f"(d[4]), "+f"(d[5]), "+f"(d[6]), "+f"(d[7]), "+f"(d[8]), "+f"(d[9]), "+f"(d[10]), "+f"(d[11]), "+f"(d[12]), "+f"(d[13]), "+f"(d[14]), "+f"(d[15]), "+f"(d[16]), "+f"(d[17]), "+f"(d[18]), "+f"(d[19]), "+f"(d[20]), "+f"(d[21]), "+f"(d[22]), "+f"(d[23]), "+f"(d[24]), "+f"(d[25]), "+f"(d[26]), "+f"(d[27]), "+f"(d[28]), "+f"(d[29]), "+f"(d[30]), "+f"(d[31])
    : "r"(a[0]), "r"(a[1]), "r"(a[2]), "r"(a[3]), "l"(desc));
}

__device__ __forceinline__ uint32_t smem_u32(const void* p) { return (uint32_t)__cvta_generic_to_shared(p); }
__device__ __forceinline__ uint64_t mkdesc(uint32_t addr, uint32_t lbo, uint32_t sbo) {
  return (uint64_t)((addr & 0x3FFFF) >> 4) | ((uint64_t)(lbo >> 4) << 16) | ((uint64_t)(sbo >> 4) << 32);
}
__device__ __forceinline__ uint32_t lds32(uint32_t a) { uint32_t v; asm volatile("ld.shared.u32 %0, [%1];" : "=r"(v) : "r"(a) : "memory"); return v; }
__device__ __forceinline__ uint4 lds128(uint32_t a) { uint4 v; asm volatile("ld.shared.v4.u32 {%0,%1,%2,%3}, [%4];" : "=r"(v.x), "=r"(v.y), "=r"(v.z), "=r"(v.w) : "r"(a) : "memory"); return v; }
__device__ __forceinline__ float ldsbf(uint32_t a) { uint16_t v; asm volatile("ld.shared.u16 %0, [%1];" : "=h"(v) : "r"(a) : "memory"); return __uint_as_float((uint32_t)v << 16); }
__device__ __forceinline__ void sts16(uint32_t a, uint32_t v) { asm volatile("st.shared.u16 [%0], %1;" :: "r"(a), "h"((uint16_t)v) : "memory"); }
__device__ __forceinline__ void sts32(uint32_t a, uint32_t v) { asm volatile("st.shared.u32 [%0], %1;" :: "r"(a), "r"(v) : "memory"); }
__device__ __forceinline__ void sts128(uint32_t a, uint32_t x, uint32_t y, uint32_t z, uint32_t w) { asm volatile("st.shared.v4.u32 [%0], {%1,%2,%3,%4};" :: "r"(a), "r"(x), "r"(y), "r"(z), "r"(w) : "memory"); }
__device__ __forceinline__ void ldsm4t(uint32_t a, uint32_t* r) {
  asm volatile("ldmatrix.sync.aligned.m8n8.x4.trans.shared.b16 {%0,%1,%2,%3}, [%4];" : "=r"(r[0]), "=r"(r[1]), "=r"(r[2]), "=r"(r[3]) : "r"(a) : "memory");
}
__device__ __forceinline__ void mma_f16(float* c, const uint32_t* a, const uint32_t* b) {
  asm volatile("mma.sync.aligned.m16n8k16.row.col.f32.f16.f16.f32 {%0,%1,%2,%3}, {%4,%5,%6,%7}, {%8,%9}, {%0,%1,%2,%3};"
    : "+f"(c[0]), "+f"(c[1]), "+f"(c[2]), "+f"(c[3]) : "r"(a[0]), "r"(a[1]), "r"(a[2]), "r"(a[3]), "r"(b[0]), "r"(b[1]));
}
__device__ __forceinline__ void stsm4(uint32_t a, const uint32_t* r) {
  asm volatile("stmatrix.sync.aligned.m8n8.x4.shared.b16 [%0], {%1,%2,%3,%4};" :: "r"(a), "r"(r[0]), "r"(r[1]), "r"(r[2]), "r"(r[3]) : "memory");
}
__device__ __forceinline__ void stsm4t(uint32_t a, const uint32_t* r) {
  asm volatile("stmatrix.sync.aligned.m8n8.x4.trans.shared.b16 [%0], {%1,%2,%3,%4};" :: "r"(a), "r"(r[0]), "r"(r[1]), "r"(r[2]), "r"(r[3]) : "memory");
}
__device__ __forceinline__ void mma_bf16(float* c, uint32_t a0, uint32_t a1, uint32_t a2, uint32_t a3, const uint32_t* b) {
  asm volatile("mma.sync.aligned.m16n8k16.row.col.f32.bf16.bf16.f32 {%0,%1,%2,%3}, {%4,%5,%6,%7}, {%8,%9}, {%0,%1,%2,%3};"
    : "+f"(c[0]), "+f"(c[1]), "+f"(c[2]), "+f"(c[3]) : "r"(a0), "r"(a1), "r"(a2), "r"(a3), "r"(b[0]), "r"(b[1]));
}
__device__ __forceinline__ void bar_sync(int id, int n) { asm volatile("bar.sync %0, %1;" :: "r"(id), "r"(n) : "memory"); }
__device__ __forceinline__ void bar_arrive(int id, int n) { asm volatile("bar.arrive %0, %1;" :: "r"(id), "r"(n) : "memory"); }
__device__ __forceinline__ float ex2f(float x) { float y; asm("ex2.approx.ftz.f32 %0, %1;" : "=f"(y) : "f"(x)); return y; }
__device__ __forceinline__ float sinaf(float x) { float y; asm("sin.approx.ftz.f32 %0, %1;" : "=f"(y) : "f"(x)); return y; }
__device__ __forceinline__ float cosaf(float x) { float y; asm("cos.approx.ftz.f32 %0, %1;" : "=f"(y) : "f"(x)); return y; }
__device__ __forceinline__ uint32_t pack_h2(float lo, float hi) { uint32_t r; asm("cvt.rn.f16x2.f32 %0, %1, %2;" : "=r"(r) : "f"(hi), "f"(lo)); return r; }
__device__ __forceinline__ uint32_t pack_bf2(float lo, float hi) { uint32_t r; asm("cvt.rn.bf16x2.f32 %0, %1, %2;" : "=r"(r) : "f"(hi), "f"(lo)); return r; }
__device__ __forceinline__ float bf_lo(uint32_t v) { return __uint_as_float(v << 16); }
__device__ __forceinline__ float bf_hi(uint32_t v) { return __uint_as_float(v & 0xffff0000u); }
__device__ __forceinline__ float bf16_round(float x) { return __bfloat162float(__float2bfloat16_rn(x)); }
__device__ __forceinline__ uint32_t hadd(uint32_t a, uint32_t b) { __nv_bfloat162 r = __hadd2(*(__nv_bfloat162*)&a, *(__nv_bfloat162*)&b); return *(uint32_t*)&r; }
__device__ __forceinline__ float exp_acc(float x) {
  const float L = 1.4426950408889634f, Ll = 1.9259629911266175e-8f;
  float t = x * L, r = fmaf(x, L, -t); r = fmaf(x, Ll, r);
  return ex2f(t) * fmaf(r, 0.6931471805599453f, 1.f);
}
__device__ __forceinline__ void mbar_init(uint32_t a, int n) { asm volatile("mbarrier.init.shared.b64 [%0], %1;" :: "r"(a), "r"(n)); }
__device__ __forceinline__ void mbar_arrive(uint32_t a) { asm volatile("mbarrier.arrive.shared.b64 _, [%0];" :: "r"(a) : "memory"); }
__device__ __forceinline__ void mbar_expect(uint32_t a, int bytes) { asm volatile("mbarrier.arrive.expect_tx.shared.b64 _, [%0], %1;" :: "r"(a), "r"(bytes) : "memory"); }
__device__ __forceinline__ void mbar_wait(uint32_t a) {
  uint32_t ok = 0; int it = 0;
  while (!ok && it++ < (1 << 20))
    asm volatile("{ .reg .pred p; mbarrier.try_wait.parity.shared.b64 p, [%1], 0, 2000; selp.u32 %0, 1, 0, p; }" : "=r"(ok) : "r"(a) : "memory");
}
__device__ __forceinline__ void warp_arrive(uint32_t a, int lane) { __syncwarp(); if (lane == 0) mbar_arrive(a); }
__device__ __forceinline__ void fence_async() { asm volatile("fence.proxy.async.shared::cta;" ::: "memory"); }
__device__ __forceinline__ uint32_t mapa(uint32_t a, uint32_t rank) { uint32_t r; asm("mapa.shared::cluster.u32 %0, %1, %2;" : "=r"(r) : "r"(a), "r"(rank)); return r; }
__device__ __forceinline__ void dsmem_copy(uint32_t dst, uint32_t src, int bytes, uint32_t mb) {
  asm volatile("cp.async.bulk.shared::cluster.shared::cta.mbarrier::complete_tx::bytes [%0], [%1], %2, [%3];" :: "r"(dst), "r"(src), "r"(bytes), "r"(mb) : "memory");
}
__device__ __forceinline__ void bulk_g2s(uint32_t dst, const void* src, int bytes, uint32_t mb) {
  asm volatile("cp.async.bulk.shared::cluster.global.mbarrier::complete_tx::bytes [%0], [%1], %2, [%3];" :: "r"(dst), "l"(src), "r"(bytes), "r"(mb) : "memory");
}
__device__ __forceinline__ void wg_fence() { asm volatile("wgmma.fence.sync.aligned;" ::: "memory"); }
__device__ __forceinline__ void wg_commit() { asm volatile("wgmma.commit_group.sync.aligned;" ::: "memory"); }
template <int N> __device__ __forceinline__ void wg_wait() { asm volatile("wgmma.wait_group.sync.aligned %0;" :: "n"(N) : "memory"); }
template <int N> __device__ __forceinline__ void fence_acc(float* d) {
  #pragma unroll
  for (int i = 0; i < N; i++) asm volatile("" : "+f"(d[i]) :: "memory");
}

struct cf { float x, y; };
__device__ __forceinline__ cf cmul(cf a, cf b) { cf r; r.x = a.x * b.x - a.y * b.y; r.y = a.x * b.y + a.y * b.x; return r; }
__device__ __forceinline__ cf cmulc(cf a, cf b) { cf r; r.x = a.x * b.x + a.y * b.y; r.y = a.y * b.x - a.x * b.y; return r; }
__device__ __forceinline__ cf csq(cf a) { cf r; r.x = a.x * a.x - a.y * a.y; r.y = (a.x + a.x) * a.y; return r; }
__device__ __forceinline__ cf cexp_fast(float a2, float th, float x) {
  float e = ex2f(a2 * x), ph = th * x; cf r; r.x = e * cosaf(ph); r.y = e * sinaf(ph); return r;
}
struct hp { uint32_t r, i; };
__device__ __forceinline__ hp hbro(cf m) { hp h; h.r = pack_h2(m.x, m.x); h.i = pack_h2(m.y, m.y); return h; }
template <bool CONJ> __device__ __forceinline__ hp hmul(hp a, hp m) {
  const __half2 ar = *(__half2*)&a.r, ai = *(__half2*)&a.i, mr = *(__half2*)&m.r, mi = CONJ ? __hneg2(*(__half2*)&m.i) : *(__half2*)&m.i;
  const __half2 x = __hfma2(ar, mr, __hneg2(__hmul2(ai, mi))), y = __hfma2(ar, mi, __hmul2(ai, mr));
  hp o; o.r = *(uint32_t*)&x; o.i = *(uint32_t*)&y; return o;
}
__device__ __forceinline__ hp hlo(hp a, hp b) { hp o; o.r = __byte_perm(a.r, b.r, 0x5410); o.i = __byte_perm(a.i, b.i, 0x5410); return o; }
__device__ __forceinline__ void put4(uint32_t a, hp p0, hp p1, hp p2, hp p3) {
  sts128(a, p0.r, p1.r, p2.r, p3.r); sts128(a + 128, p0.i, p1.i, p2.i, p3.i);
}

struct Pow { hp t0, z, m2, m4, m256, m512, m1024, b0, m16, m32; uint32_t m64, m128; };
__device__ __forceinline__ void gen_powers(Pow& p, float al, float tt, cf c) {
  const cf w1 = cexp_fast(al, tt, 1.f), w64 = cexp_fast(al, tt, 64.f);
  const cf w2 = csq(w1), w4 = csq(w2), w8 = csq(w4), w16 = csq(w8), w32 = csq(w16);
  const cf w128 = csq(w64), w256 = csq(w128), w512 = csq(w256), w1024 = csq(w512);
  const cf c1 = cmulc(c, w1), c512 = cmulc(c, w512), c768 = cmulc(c512, w256);
  p.t0.r = pack_h2(c.x, c1.x); p.t0.i = pack_h2(c.y, c1.y);
  p.z.r = pack_h2(c512.x, c768.x); p.z.i = pack_h2(c512.y, c768.y);
  p.m2 = hbro(w2); p.m4 = hbro(w4); p.m256 = hbro(w256); p.m512 = hbro(w512); p.m1024 = hbro(w1024);
  p.b0.r = pack_h2(1.f, w8.x); p.b0.i = pack_h2(0.f, w8.y);
  p.m16 = hbro(w16); p.m32 = hbro(w32); p.m64 = pack_h2(w64.x, w64.y); p.m128 = pack_h2(w128.x, w128.y);
}
constexpr int KSLOT = 1024;
__device__ __forceinline__ void gen_store(const Pow& p, uint32_t gb, uint32_t gm) {
  const uint32_t bb = gb + 256;
  hp t1 = hmul<true>(p.t0, p.m2), t2 = hmul<true>(p.t0, p.m4), t3 = hmul<true>(t1, p.m4);
  put4(bb, p.t0, t1, t2, t3);
  const hp z4 = hmul<true>(p.z, p.m4);
  hp u0, u1; u0.r = __byte_perm(p.z.r, z4.r, 0x5410); u0.i = __byte_perm(p.z.i, z4.i, 0x5410);
  u1.r = __byte_perm(p.z.r, z4.r, 0x7632); u1.i = __byte_perm(p.z.i, z4.i, 0x7632);
  put4(bb + 256, hmul<true>(hlo(p.t0, t1), p.m256), hmul<true>(hlo(t2, t3), p.m256), u0, u1);
  u0 = hmul<true>(p.z, p.m512); u1 = hmul<true>(p.z, p.m1024);
  const hp u2 = hmul<true>(u0, p.m1024);
  put4(bb + 512, u0, u1, u2, u2);
  t1 = hmul<false>(p.b0, p.m16); t2 = hmul<false>(p.b0, p.m32); t3 = hmul<false>(t1, p.m32);
  put4(gb, p.b0, t1, t2, t3);
  sts16(gm, p.m64); sts16(gm + 4, p.m64 >> 16); sts16(gm + 128, p.m128); sts16(gm + 132, p.m128 >> 16);
  __syncwarp();
}
__device__ __forceinline__ void gen_contract(float* d, uint32_t la, uint32_t lb, uint32_t lm, uint32_t zr) {
  #pragma unroll
  for (int ks = 0; ks < 4; ks++) {
    uint32_t fa[4], fc[4], fb[8];
    ldsm4t(la + ks * KSLOT, fb + 4);
    hp m64, m128, x, y;
    asm volatile("ld.shared.v2.u32 {%0,%1}, [%2];" : "=r"(m64.r), "=r"(m64.i) : "r"(lm + ks * 32) : "memory");
    asm volatile("ld.shared.v2.u32 {%0,%1}, [%2];" : "=r"(m128.r), "=r"(m128.i) : "r"(lm + ks * 32 + 128) : "memory");
    ldsm4t(lb + ks * KSLOT, fb);
    x.r = fb[6]; x.i = fb[7]; y = hmul<false>(x, m64);
    fa[0] = x.r + zr; fa[2] = x.i + zr; fa[1] = y.r; fa[3] = y.i;
    x = hmul<false>(x, m128); y = hmul<false>(y, m128);
    fc[0] = x.r; fc[2] = x.i; fc[1] = y.r; fc[3] = y.i;
    #pragma unroll
    for (int nt = 0; nt < 3; nt++) { mma_f16(d + 4 * nt, fa, fb + 2 * nt); mma_f16(d + 12 + 4 * nt, fc, fb + 2 * nt); }
  }
  __syncwarp();
}

template <int S> __device__ __forceinline__ void near_step(float* d, uint64_t ud, const uint32_t* a) {
  constexpr int arr = (S & 1) ? 0 : 2;
  constexpr int slot = (S & 1) ? (S - 1) / 2 : S / 2;
  const uint64_t desc = ud + (uint64_t)((arr * UA_ARR + slot * 16) >> 4);
  if constexpr (S < 16) wgmma_n64(d, a, desc);
  else if constexpr (S < 32) wgmma_n56(d, a, desc);
  else if constexpr (S < 34) wgmma_n48(d, a, desc);
  else if constexpr (S == 63) wgmma_n40(d, a, desc);
  else wgmma_n32(d, a, desc);
}
template <int S0, int NS> __device__ __forceinline__ void near_load(uint32_t (*a)[4], uint32_t wa, uint32_t zr) {
  a[0][2] = lds32(wa + (uint32_t)((2 * S0 - 1) * 32));
  #pragma unroll
  for (int i = 0; i < NS; i++) {
    a[i][0] = lds32(wa + (2 * (S0 + i)) * 32);
    a[i][1] = lds32(wa + (2 * (S0 + i) + 1) * 32);
  }
  #pragma unroll
  for (int i = 0; i < NS; i++) {
    a[i][3] = a[i][0] + zr;
    if (i + 1 < NS) a[i + 1][2] = a[i][1] + zr;
  }
}
template <int S0, int NS> __device__ __forceinline__ void near_issue(float* d, uint64_t ua, uint32_t (*a)[4]) {
  wg_fence();
  near_step<S0>(d, ua, a[0]);
  if constexpr (NS > 1) near_step<S0 + 1>(d, ua, a[1]);
  if constexpr (NS > 2) near_step<S0 + 2>(d, ua, a[2]);
  if constexpr (NS > 3) near_step<S0 + 3>(d, ua, a[3]);
  if constexpr (NS > 4) near_step<S0 + 4>(d, ua, a[4]);
  if constexpr (NS > 5) near_step<S0 + 5>(d, ua, a[5]);
  wg_commit();
}

__device__ __forceinline__ void sts2x(uint32_t o, const uint32_t* w) {
  const bool sw = (threadIdx.x >> 2) & 1;
  sts128(o + (sw ? 16 : 0), sw ? w[4] : w[0], sw ? w[5] : w[1], sw ? w[6] : w[2], sw ? w[7] : w[3]);
  sts128(o + (sw ? 0 : 16), sw ? w[0] : w[4], sw ? w[1] : w[5], sw ? w[2] : w[6], sw ? w[3] : w[7]);
}
__device__ __forceinline__ void ytab_chunk(uint32_t ub, uint32_t yb, int chi) {
  auto ca = [&](int c) { return ub + (c & 3) * UA_ARR - (c >> 2) * 16; };
  const uint4 z = lds128(ca(chi - 2)), a = lds128(ca(chi - 1)), b = lds128(ca(chi)), c = lds128(ca(chi + 1));
  const float v[23] = {bf_hi(z.z), bf_lo(z.w), bf_hi(z.w),
                       bf_lo(a.x), bf_hi(a.x), bf_lo(a.y), bf_hi(a.y), bf_lo(a.z), bf_hi(a.z), bf_lo(a.w), bf_hi(a.w),
                       bf_lo(b.x), bf_hi(b.x), bf_lo(b.y), bf_hi(b.y), bf_lo(b.z), bf_hi(b.z), bf_lo(b.w), bf_hi(b.w),
                       bf_lo(c.x), bf_hi(c.x), bf_lo(c.y), bf_hi(c.y)};
  float s[24];
  s[13] = 0.f; s[14] = v[13]; s[12] = -v[12];
  #pragma unroll
  for (int i = 15; i < 24; i++) s[i] = s[i - 1] + v[i - 1];
  #pragma unroll
  for (int i = 11; i >= 0; i--) s[i] = s[i + 1] - v[i];
  uint32_t w[8];
  {
    #pragma unroll
    for (int i = 0; i < 8; i++) w[i] = pack_bf2(s[i + 14] - s[i + 9], s[i + 9] - s[i + 6]);
    const int cp = (chi ^ ((chi >> 2) & 1)) * 32;
    uint32_t o = yb + Y2_OFF + cp;
    sts2x(o, w);
    if (chi < 128) {
      #pragma unroll
      for (int i = 0; i < 8; i++) w[i] = pack_bf2(s[i + 16] - s[i + 7], s[i + 7] - s[i]);
      o = yb + Y3_OFF + cp;
      sts2x(o, w);
    }
  }
}

__device__ __forceinline__ uint32_t ldv32(uint32_t a) { uint32_t v; asm volatile("ld.volatile.shared.u32 %0, [%1];" : "=r"(v) : "r"(a) : "memory"); return v; }
__device__ __forceinline__ void ld_frag(uint32_t* n, uint32_t x, int dp, int dm) { n[0] = ldv32(x); n[1] = ldv32(x + dp); n[2] = ldv32(x + dm); }
__device__ __forceinline__ void far_octet(float (*acc)[4], int j0, uint32_t yb, uint32_t kb, int g, int q, const uint32_t (*b2)[2]) {
  const int mu = g >> 1;
  const uint32_t zr = ldv32(kb);
  uint32_t a[4][4];
  const int dp = q < 2 ? -32 : 32;
  if (j0 >= 4) {
    const uint32_t ya = yb + Y2_OFF + (64 * (j0 - 8) + 48 - 16 * q + (q < 2 ? 8 : 0) + g) * 4;
    const int dm = (q == 0) ? -96 : (q == 2) ? -32 : -64;
    #pragma unroll
    for (int i = 0; i < 3; i++) ld_frag(a[i], ya + (3 - i) * 256, dp, dm);
    #pragma unroll
    for (int i = 0; i < 12; i++) {
      const int br = 3 - i;
      if ((i & 3) == 1 && j0 + br < 7) break;
      if (i + 3 < 12) ld_frag(a[(i + 3) & 3], ya + (br - 3) * 256, dp, dm);
      uint32_t* c = a[i & 3];
      c[3] = c[0] + zr;
      #pragma unroll
      for (int j = 0; j < 4; j++) { const int s = j - br; if (s >= 0 && s < 9) mma_bf16(acc[j], c[0], c[1], c[2], c[3], b2[s]); }
    }
  }
  if (j0 >= 12) {
    const uint32_t ya = yb + Y3_OFF + (64 * (j0 - 16) + 48 - 16 * q + (q < 2 ? 8 : 0) + g) * 4;
    #pragma unroll
    for (int i = 0; i < 3; i++) { a[i][0] = ldv32(ya + (3 - i) * 256); a[i][1] = ldv32(ya + (3 - i) * 256 + dp); }
    uint32_t b3[9][2];
    #pragma unroll
    for (int s = 0; s < 9; s++) { b3[s][0] = ldv32(kb + (TW_3 + mu + q + 8 * s) * 4); b3[s][1] = ldv32(kb + (TW_3 + mu + q + 8 * s + 4) * 4); }
    #pragma unroll
    for (int i = 0; i < 17; i++) {
      const int br = 3 - i;
      if ((i & 3) == 1 && j0 + br < 15) break;
      if (i + 3 < 18) { uint32_t* n = a[(i + 3) & 3]; n[0] = ldv32(ya + (br - 3) * 256); n[1] = ldv32(ya + (br - 3) * 256 + dp); }
      uint32_t* c = a[i & 3];
      c[2] = a[(i + 1) & 3][0] + zr; c[3] = a[(i + 1) & 3][1] + zr;
      #pragma unroll
      for (int j = 0; j < 4; j++) { const int s2 = j - br; if (s2 >= 0 && !(s2 & 1)) mma_bf16(acc[j], c[0], c[1], c[2], c[3], b3[s2 >> 1]); }
    }
  }
}

__global__ void __cluster_dims__(2, 1, 1) __launch_bounds__(NTHR, 1)
ssm_gated_kernel(const __grid_constant__ CUtensorMap tmap_u, const __grid_constant__ CUtensorMap tmap_o, const __grid_constant__ Params P) {
  extern __shared__ __align__(1024) unsigned char smem[];
  const uint32_t sb = smem_u32(smem);
  const int tid = threadIdx.x, warp = __shfl_sync(~0u, tid >> 5, 0), lane = tid & 31;
  const int g = lane >> 2, q = lane & 3;
  const int cta = blockIdx.x, c0 = cta * 4, rank = cta & 1;
  const uint32_t mb = sb + SM_BAR;
  if (tid == 0) {
    mbar_init(mb + MB_PRM, 1); mbar_init(mb + MB_ROW, 1);
    fence_async();
    mbar_expect(mb + MB_PRM, 10240 + 64);
    #pragma unroll
    for (int i = 0; i < 10; i++) bulk_g2s(sb + SM_PRM + i * 1024, P.pm[i] + c0 * NMODE, 1024, mb + MB_PRM);
    #pragma unroll
    for (int i = 0; i < 4; i++) bulk_g2s(sb + SM_PRM + 10240 + i * 16, P.pv[i] + (cta >> 1) * 8, 16, mb + MB_PRM);
    mbar_expect(mb + MB_ROW, 16384 + 1024);
    bulk_g2s(sb + SM_ROW, P.u + (size_t)cta * 16 * DIM, 16384, mb + MB_ROW);
    bulk_g2s(sb + SM_ROW + 16384, P.gate_w, 1024, mb + MB_ROW);
  }
  if (tid == 32) {
    mbar_init(mb + MB_U, 1); mbar_init(mb + MB_URDY, 1);
    mbar_init(mb + MB_G1, 8); mbar_init(mb + MB_G23, 8); mbar_init(mb + MB_PEER, 1); mbar_init(mb + MB_GW, 4);
    #pragma unroll
    for (int i = 0; i < 4; i++) mbar_init(mb + MB_Y + 8 * i, 8);
    #pragma unroll
    for (int i = 0; i < 8; i++) { mbar_init(mb + MB_LOC + 8 * i, i ? 20 : 16); mbar_init(mb + MB_RX + 8 * i, 1); }
    asm volatile("fence.mbarrier_init.release.cluster;" ::: "memory");
    fence_async();
  }
  STAMP(0);

  if (warp < 16) {
    const int ch = warp >> 2, br = (warp >> 1) & 1, w0 = warp & 1;
    asm volatile("setmaxnreg.inc.sync.aligned.u32 96;");
    for (int i = tid; i < (SM_Y01 - SM_UA) / 16; i += 512) sts128(sb + SM_UA + i * 16, 0, 0, 0, 0);
    asm volatile("barrier.cluster.arrive.relaxed.aligned;" ::: "memory");
    bar_sync(0, NTHR);
    const uint32_t tab = sb + SM_TAB + (ch * 2 + br) * TAB_SZ;
    const uint32_t zr = lds32(tab);
    const uint32_t yb = sb + (ch < 2 ? SM_Y01 + ch * Y_CH : SM_Y23 + (ch - 2) * 8 * GSLOT);
    {
      const uint32_t gw = sb + SM_G + warp * (2 * GSLOT);
      const uint32_t gb = gw + (lane >> 3) * KSLOT + (lane & 7) * 16;
      const uint32_t gm = gw + 4 * KSLOT + (lane >> 1) * 8 + (lane & 1) * 2;
      const uint32_t la = gw + (((lane >> 3) * 128 + 768) & 1023) + (lane & 7) * 16;
      const uint32_t lb = gw + 256 + (lane >> 3) * 128 + (lane & 7) * 16;
      const uint32_t lm = gw + 4 * KSLOT + q * 8;
      float a2[2], th[2]; cf cc[2];
      const uint32_t pp = sb + SM_PRM + br * 4096 + ch * 256 + (w0 * 32 + lane) * 2;
      const uint32_t pl = sb + SM_PRM + 10240 + br * 16 + rank * 8 + ch * 2;
      mbar_wait(mb + MB_PRM);
      STAMP(1);
      const float dt = bf16_round(exp_acc(ldsbf(pl)));
      float mxf = 0.f;
      #pragma unroll
      for (int r = 0; r < 2; r++) {
        float are = ldsbf(pp + r * 128);
        if (br) are = -bf16_round(exp_acc(are));
        a2[r] = (are * dt) * 1.4426950408889634f; th[r] = ldsbf(pp + r * 128 + 1024) * dt;
        cf c = {ldsbf(pp + r * 128 + 2048), ldsbf(pp + r * 128 + 3072)}, dB = {dt + dt, 0.f};
        if (!br) { dB.x = dt * ldsbf(pp + r * 128 + 8192); dB.y = dt * ldsbf(pp + r * 128 + 9216); }
        c = cmul(c, dB); cc[r].x = c.x; cc[r].y = -c.y;
        mxf = fmaxf(mxf, fmaxf(fabsf(c.x), fabsf(c.y)));
      }
      const int e = min(max((int)(__reduce_max_sync(~0u, __float_as_uint(mxf)) >> 23), 1), 252);
      const float sc = __uint_as_float((uint32_t)(253 - e) << 23);
      float d[24];
      #pragma unroll
      for (int i = 0; i < 24; i++) d[i] = 0.f;
      {
        Pow p;
        cf c = cc[0]; c.x *= sc; c.y *= sc;
        gen_powers(p, a2[0], th[0], c);
        gen_store(p, gb, gm);
        STAMP(2);
        c = cc[1]; c.x *= sc; c.y *= sc;
        gen_powers(p, a2[1], th[1], c);
        gen_contract(d, la, lb, lm, zr);
        gen_store(p, gb, gm);
        STAMP(3);
        gen_contract(d, la, lb, lm, zr);
      }
      const float isc = __uint_as_float((uint32_t)(e + 1) << 23);
      const int jr = w0 * 16 + g;
      const uint32_t a0 = tab + (TW_W + 8 * jr + 2 * q) * 4;
      const uint32_t a1 = tab + (q < 2 ? TW_W + 256 + 8 * jr + 4 * q : TW_2 + 6 + 32 * (q - 2) + jr) * 4;
      const uint32_t a3 = tab + TW_3 * 4 + (6 + 64 * q + jr) * 2;
      float k[12];
      {
        #pragma unroll
        for (int i = 0; i < 3; i++) {
          sts128(gw + i * 512 + lane * 16, __float_as_uint((w0 ? d[4 * i] : d[12 + 4 * i]) * isc), __float_as_uint((w0 ? d[4 * i + 1] : d[13 + 4 * i]) * isc),
                 __float_as_uint((w0 ? d[4 * i + 2] : d[14 + 4 * i]) * isc), __float_as_uint((w0 ? d[4 * i + 3] : d[15 + 4 * i]) * isc));
        }
        const float own = (lane == 0 ? d[8] : d[4]) * isc;
        if (!w0 && (lane == 0 || lane == 2)) sts32(gw + 1536 + lane * 2, __float_as_uint(own));
        const float fo = __shfl_sync(~0u, own, q == 3 ? 0 : 2);
        bar_sync(1 + ch, 128);
        const uint32_t po = sb + SM_G + (warp ^ 1) * (2 * GSLOT) + lane * 16;
        #pragma unroll
        for (int i = 0; i < 3; i++) {
          const uint4 v = lds128(po + i * 512);
          k[4 * i]     = fmaf(w0 ? d[12 + 4 * i] : d[4 * i], isc, __uint_as_float(v.x));
          k[4 * i + 1] = fmaf(w0 ? d[13 + 4 * i] : d[4 * i + 1], isc, __uint_as_float(v.y));
          k[4 * i + 2] = fmaf(w0 ? d[14 + 4 * i] : d[4 * i + 2], isc, __uint_as_float(v.z));
          k[4 * i + 3] = fmaf(w0 ? d[15 + 4 * i] : d[4 * i + 3], isc, __uint_as_float(v.w));
        }
        if (w0 && g == 7 && (q & 1)) k[7] -= fo + __uint_as_float(lds32(po - lane * 16 + 1536 + (q == 3 ? 0 : 4)));
        warp_arrive(mb + (ch < 2 ? MB_G1 : MB_G23), lane);
      }
      if (jr == 0 && q == 0) k[0] += ldsbf(pl + 32);
      #pragma unroll
      for (int h = 0; h < 2; h++) {
        uint32_t w = pack_bf2(k[2 * h + 1], k[2 * h]);
        sts16(a0 + h * 256, w >> 16); sts32(a0 + h * 256 + 4, w); sts16(a0 + h * 256 + 10, w);
        w = pack_bf2(k[4 + 2 * h], k[5 + 2 * h]);
        if (q < 2) {
          const uint32_t a = a1 + h * 256, w0w = __byte_perm(w, w, 0x1010);
          if (h == 0 && jr == 0 && q == 0) sts16(a, w0w); else { sts16(a - 4, w0w); sts32(a, w0w); }
          sts32(a + 4, w0w); sts32(a + 8, __byte_perm(w, w, 0x1032)); sts16(a + 14, w >> 16);
        } else sts32(a1 + h * 32, w);
        w = pack_bf2(k[8 + 2 * h], k[9 + 2 * h]);
        if (q < 2 || (q == 2 && h == 0 && jr == 0)) sts16(a3 + h * 16, w);
        if (q < 2) sts16(a3 + h * 16 + 64, w >> 16);
        if (h == 0 && jr == 0 && q == 0) { sts16(tab + (TW_X + 1019 - 976) * 4, w); sts16(tab + (TW_X + 1020 - 976) * 4 + 2, w); }
      }
      bar_sync(1 + ch, 128);
      STAMP(4);
    }
    {
      const uint64_t ua = mkdesc(sb + SM_UA + ch * UA_CH, UA_ARR, 128);
      const uint32_t wa = tab + (TW_W + 16 * w0 + g - 2 * q - 16) * 4;
      float d[32];
      #pragma unroll
      for (int i = 0; i < 32; i++) d[i] = 0.f;
      uint32_t A[4][4], B[4][4];
      near_load<0, 4>(A, wa, zr);
      near_load<4, 4>(B, wa, zr);
      STAMP(6);
      mbar_wait(mb + MB_URDY);
      STAMP(7);
      fence_acc<32>(d);
      near_issue<0, 4>(d, ua, A);
      near_issue<4, 4>(d, ua, B);   wg_wait<1>();
      near_load<8, 4>(A, wa, zr);   near_issue<8, 4>(d, ua, A);   wg_wait<1>();
      near_load<12, 4>(B, wa, zr);  near_issue<12, 4>(d, ua, B);  wg_wait<1>();
      near_load<16, 4>(A, wa, zr);  near_issue<16, 4>(d, ua, A);  wg_wait<1>();
      near_load<20, 4>(B, wa, zr);  near_issue<20, 4>(d, ua, B);  wg_wait<1>();
      near_load<24, 4>(A, wa, zr);  near_issue<24, 4>(d, ua, A);  wg_wait<1>();
      near_load<28, 4>(B, wa, zr);  near_issue<28, 4>(d, ua, B);  wg_wait<1>();
      near_load<32, 2>(A, wa, zr);  near_issue<32, 2>(d, ua, A);  wg_wait<1>();
      near_load<63, 3>(B, wa - (uint32_t)((976 + TW_W - TW_X) * 4), zr);
      near_issue<63, 1>(d, ua, B);
      near_issue<64, 2>(d, ua, B + 1);
      wg_wait<0>();
      fence_acc<32>(d);
      mbar_wait(mb + MB_GW);
      mbar_wait(mb + MB_G1);
      STAMP(8);
      const int m = lane >> 3, tl = 7 - (lane & 7);
      const uint32_t ga = sb + SM_GW + br * 5120 + ((3 - q) * 40 + 16 * w0 + g) * 4;
      const int c16 = 4 * (tl & 3) + 2 * w0 + (m & 1);
      const uint32_t ta = sb + SM_T + (m >> 1) * 4096 + (tl >> 2) * 2048 + (br * 4 + ch) * 256 + ((c16 ^ (tl >> 1) ^ (rank * 4 + ch)) * 16);
      #pragma unroll
      for (int i = 0; i < 8; i += 2) {
        uint32_t r[4];
        #pragma unroll
        for (int kk = 0; kk < 4; kk++) {
          const int ii = i + (kk >> 1), h = kk & 1;
          const uint32_t gw = lds32(ga + (ii * 160 + 8 * h) * 4);
          const uint32_t y = pack_bf2(d[4 * (7 - ii) + 2 * h], d[4 * (7 - ii) + 2 * h + 1]);
          const __nv_bfloat162 t2 = __hmul2(*(const __nv_bfloat162*)&y, *(const __nv_bfloat162*)&gw);
          r[kk] = *(const uint32_t*)&t2;
        }
        stsm4t(ta + i * 4096, r);
        __syncwarp();
        if (lane < 2) mbar_arrive(mb + MB_LOC + 8 * (i + lane));
      }
    }
    STAMP(9);
    {
      const uint32_t kb = sb + SM_TAB + (ch * 2 + (g & 1)) * TAB_SZ;
      uint32_t b2[9][2];
      #pragma unroll
      for (int s = 0; s < 9; s++)
        asm volatile("ld.shared.v2.u32 {%0,%1}, [%2];" : "=r"(b2[s][0]), "=r"(b2[s][1]) : "r"(kb + (TW_2 + 2 * (g >> 1) + 2 * q + 8 * s) * 4) : "memory");
      mbar_wait(mb + MB_Y + 8 * ch);
      STAMP(10);
      const int c32 = lane, c16 = c32 & 15;
      const uint32_t t3a = sb + SM_T3 + (c32 >> 4) * 1024 + ch * 256 + ((c16 ^ (c32 >> 3) ^ (rank * 4 + ch)) * 16);
      #pragma unroll 1
      for (int ps = 0; ps < 2; ps++) {
        const int o4 = (warp + ch) & 3, oc = ps ? o4 + 4 : o4, j0 = 4 * oc;
        if (oc == 0) continue;
        float acc[4][4];
        uint32_t gq[4];
        #pragma unroll
        for (int j = 0; j < 4; j++) {
          gq[j] = lds32(sb + SM_GE + (32 * (j0 + j) + 8 * q + g) * 4);
          acc[j][0] = acc[j][1] = acc[j][2] = acc[j][3] = 0.f;
        }
        far_octet(acc, j0, yb, kb, g, q, b2);
        uint32_t r[4];
        #pragma unroll
        for (int j = 0; j < 4; j++)
          r[j] = pack_bf2(fmaf(bf_lo(gq[j]), acc[j][0] - acc[j][1], acc[j][1]), fmaf(bf_hi(gq[j]), acc[j][2] - acc[j][3], acc[j][3]));
        stsm4t(t3a + oc * 2048, r);
        warp_arrive(mb + MB_LOC + 8 * oc, lane);
        STAMP(11 + ps);
      }
    }
  } else {
    asm volatile("setmaxnreg.dec.sync.aligned.u32 48;");
    const int aw = warp - 16, at = tid - 512;
    const uint32_t epoch = __ldcg(&g_epoch[cta]) + 1u, tag = epoch & 0xffffu;
    asm volatile("barrier.cluster.arrive.relaxed.aligned;" ::: "memory");
    bar_sync(0, NTHR);
    STAMP(1);
    if (aw >= 4) {
      const int bw = aw - 4, bt = at - 128;
      if (bt == 0) {
        mbar_expect(mb + MB_U, 16384);
        #pragma unroll
        for (int i = 0; i < 4; i++)
          asm volatile("cp.async.bulk.tensor.2d.shared::cluster.global.mbarrier::complete_tx::bytes [%0], [%1, {%3, %4}], [%2];"
                       :: "r"(sb + SM_RAW + i * 4096), "l"((uint64_t)&tmap_u), "r"(mb + MB_U), "r"((cta >> 1) * 8), "r"(rank * 1024 + i * 256) : "memory");
        mbar_expect(mb + MB_PEER, 8192);
        #pragma unroll
        for (int i = 0; i < 8; i++) mbar_expect(mb + MB_RX + 8 * i, 1024);
      }
      mbar_wait(mb + MB_U);
      STAMP(2);
      const int chs = (lane & 7) - rank * 4, m = lane >> 3;
      const uint32_t base = ((unsigned)chs < 4u) ? sb + SM_UA + chs * UA_CH + m * UA_ARR + (63 - rank * 32) * 16
                                                 : sb + SM_XS + 64 + (chs & 3) * XS_CH + m * 512 + 31 * 16;
      #pragma unroll
      for (int hh = 0; hh < 2; hh++) {
        uint32_t r[4][4];
        #pragma unroll
        for (int it = 0; it < 4; it++) ldsm4t(sb + SM_RAW + ((bw * 8 + hh * 4 + it) * 32 + lane) * 16, r[it]);
        #pragma unroll
        for (int it = 0; it < 4; it++) stsm4(base - (bw * 8 + hh * 4 + it) * 16, r[it]);
      }
      fence_async();
      asm volatile("barrier.cluster.wait.aligned;" ::: "memory");
      bar_sync(11, 128);
      if (lane < 4) {
        dsmem_copy(mapa(sb + SM_UA + bw * UA_CH + lane * UA_ARR + (32 - rank * 32) * 16, rank ^ 1),
                   sb + SM_XS + 64 + bw * XS_CH + lane * 512, 512, mapa(mb + MB_PEER, rank ^ 1));
      }
      STAMP(3);
      mbar_wait(mb + MB_PEER);
      if (bt == 0) mbar_arrive(mb + MB_URDY);
      STAMP(4);
    } else {
      mbar_wait(mb + MB_ROW);
      {
        const uint4 gw0 = lds128(sb + SM_ROW + 16384 + lane * 16), gw1 = lds128(sb + SM_ROW + 16384 + 512 + lane * 16);
        float s[4];
        #pragma unroll
        for (int r = 0; r < 4; r++) {
          const uint4 x0 = lds128(sb + SM_ROW + (aw * 4 + r) * 1024 + lane * 16), x1 = lds128(sb + SM_ROW + (aw * 4 + r) * 1024 + 512 + lane * 16);
          const uint32_t xv[8] = {x0.x, x0.y, x0.z, x0.w, x1.x, x1.y, x1.z, x1.w}, wv[8] = {gw0.x, gw0.y, gw0.z, gw0.w, gw1.x, gw1.y, gw1.z, gw1.w};
          float a = 0.f, b = 0.f;
          #pragma unroll
          for (int i = 0; i < 8; i++) {
            __nv_bfloat162 pr2 = __hmul2(*(const __nv_bfloat162*)&xv[i], *(const __nv_bfloat162*)&wv[i]);
            const uint32_t pv = *(uint32_t*)&pr2;
            a += bf_lo(pv); b += bf_hi(pv);
          }
          s[r] = a + b;
        }
        float t0 = (lane & 1) ? s[1] : s[0], t1 = (lane & 1) ? s[3] : s[2];
        t0 += __shfl_xor_sync(~0u, (lane & 1) ? s[0] : s[1], 1); t1 += __shfl_xor_sync(~0u, (lane & 1) ? s[2] : s[3], 1);
        float t = (lane & 2) ? t1 : t0;
        t += __shfl_xor_sync(~0u, (lane & 2) ? t0 : t1, 2);
        #pragma unroll
        for (int o = 4; o < 32; o <<= 1) t += __shfl_xor_sync(~0u, t, o);
        if (lane < 4) {
          const float gv = __fdividef(1.f, 1.f + exp_acc(-bf16_round(t)));
          const uint32_t w = (pack_bf2(gv, gv) & 0xffffu) | (tag << 16);
          asm volatile("st.relaxed.gpu.global.u32 [%0], %1;" :: "l"(&g_gate[cta * 16 + aw * 4 + lane]), "r"(w) : "memory");
        }
      }
      STAMP(2);
      asm volatile("barrier.cluster.wait.aligned;" ::: "memory");
      mbar_wait(mb + MB_URDY);
      if (at == 0) __stcg(&g_epoch[cta], epoch);
      #pragma unroll 1
      for (int kk = 0; kk < 2; kk++) {
        uint32_t x[4], y[4]; int it = 0; bool ok;
        do {
          ok = true;
          #pragma unroll
          for (int k = 0; k < 4; k++) {
            const uint32_t* gp = &g_gate[64 * (aw + 4 * k + 16 * kk) + lane];
            asm volatile("ld.relaxed.gpu.global.u32 %0, [%1];" : "=r"(x[k]) : "l"(gp) : "memory");
            asm volatile("ld.relaxed.gpu.global.u32 %0, [%1];" : "=r"(y[k]) : "l"(gp + 32) : "memory");
          }
          #pragma unroll
          for (int k = 0; k < 4; k++) ok = ok && (x[k] >> 16) == tag && (y[k] >> 16) == tag;
        } while (!ok && ++it < (1 << 18));
        #pragma unroll
        for (int k = 0; k < 4; k++) {
          uint32_t a = sb + SM_GW + ((aw + 4 * k + 16 * kk) * 40 + lane) * 4;
          sts32(a, __byte_perm(y[k], x[k], 0x5410));
          sts32(a + 5120, pack_bf2(1.f - bf_lo(y[k]), 1.f - bf_lo(x[k])));
          const uint32_t ge = sb + SM_GE + ((aw + 4 * k + 16 * kk) * 32 + (lane >> 4) * 8 + (lane & 7)) * 4 + ((lane >> 3) & 1) * 2;
          sts16(ge, x[k]); sts16(ge + 64, y[k]);
        }
      }
      warp_arrive(mb + MB_GW, lane);
      STAMP(4);
    }
    bar_sync(12, 256);
    #pragma unroll 1
    for (int c = 0; c < 4; c++) {
      const uint32_t yb = sb + (c < 2 ? SM_Y01 + c * Y_CH : SM_Y23 + (c - 2) * 8 * GSLOT);
      if (c == 0) mbar_wait(mb + MB_G23);
      if (at >= 200) {
        const int i = at - 200;
        sts128(yb + (i < 28 ? i * 16 : Y3_OFF - 512 + (i - 28) * 16), 0, 0, 0, 0);
      }
      if (at >= 6 && at < 200) ytab_chunk(sb + SM_UA + c * UA_CH + 63 * 16, yb, at - 8);
      warp_arrive(mb + MB_Y + 8 * c, lane);
      STAMP(5 + c);
    }
    {
      const int k = aw;
      const uint32_t tk = sb + SM_T + k * 4096 + lane * 16, t3 = sb + SM_T3 + k * 2048 + lane * 16;
      mbar_wait(mb + MB_LOC + 8 * k);
      STAMP(11);
      #pragma unroll
      for (int i = 0; i < 4; i++) {
        const int hf = (i >> 1) ^ rank ^ 1, o = (i & 1) * 512;
        const uint4 a = lds128(tk + hf * 2048 + o), b = lds128(tk + hf * 2048 + 1024 + o), c = k ? lds128(t3 + hf * 1024 + o) : make_uint4(0, 0, 0, 0);
        const uint32_t s0 = hadd(hadd(a.x, b.x), c.x), s1 = hadd(hadd(a.y, b.y), c.y), s2 = hadd(hadd(a.z, b.z), c.z), s3 = hadd(hadd(a.w, b.w), c.w);
        if (i < 2)
          asm volatile("st.async.weak.shared::cluster.mbarrier::complete_tx::bytes.v4.u32 [%0], {%1,%2,%3,%4}, [%5];"
                       :: "r"(mapa(sb + SM_RX + k * 1024 + lane * 16 + o, rank ^ 1)), "r"(s0), "r"(s1), "r"(s2), "r"(s3), "r"(mapa(mb + MB_RX + 8 * k, rank ^ 1)) : "memory");
        else sts128(t3 + hf * 1024 + o, s0, s1, s2, s3);
      }
      __syncwarp();
      mbar_wait(mb + MB_RX + 8 * k);
      STAMP(12);
      const int m = lane >> 3, j = lane & 7;
      const uint32_t src = (((j >> 2) == rank) ? sb + SM_T3 + k * 2048 + rank * 1024 : sb + SM_RX + k * 1024) + (j & 3) * 256;
      const uint32_t ob = sb + SM_T + k * 4096;
      #pragma unroll
      for (int it = 0; it < 4; it++) {
        const int c16 = 4 * it + m;
        uint32_t r[4];
        ldsm4t(src + ((c16 ^ (rank * 2 + (c16 >> 3)) ^ j) * 16), r);
        stsm4(ob + (it * 32 + lane) * 16, r);
      }
      fence_async();
      __syncwarp();
      if (lane == 0) {
        asm volatile("cp.async.bulk.tensor.2d.global.shared::cta.bulk_group [%0, {%2, %3}], [%1];"
                     :: "l"((uint64_t)&tmap_o), "r"(ob), "r"((cta >> 1) * 8), "r"(k * 256 + rank * 128) : "memory");
        asm volatile("cp.async.bulk.commit_group;" ::: "memory");
        asm volatile("cp.async.bulk.wait_group.read 0;" ::: "memory");
      }
      __syncwarp();
      STAMP(13);
    }
    asm volatile("barrier.cluster.arrive.relaxed.aligned;" ::: "memory");
    asm volatile("barrier.cluster.wait.aligned;" ::: "memory");
    STAMP(14);
    STAMP_DUMP();
  }
}

typedef CUresult (*EncodeFn)(CUtensorMap*, CUtensorMapDataType, cuuint32_t, void*, const cuuint64_t*, const cuuint64_t*,
                             const cuuint32_t*, const cuuint32_t*, CUtensorMapInterleave, CUtensorMapSwizzle,
                             CUtensorMapL2promotion, CUtensorMapFloatOOBfill);
}

extern "C" void kernel_launch(void* const* d_in, const int* in_sizes, int n_in, void* d_out, int out_size) {
  (void)in_sizes; (void)n_in; (void)out_size;
  static EncodeFn enc = nullptr;
  if (!enc) {
    void* fn = nullptr; cudaDriverEntryPointQueryResult qr;
    cudaGetDriverEntryPoint("cuTensorMapEncodeTiled", &fn, cudaEnableDefault, &qr);
    enc = (EncodeFn)fn;
    cudaFuncSetAttribute(ssm_gated_kernel, cudaFuncAttributeMaxDynamicSharedMemorySize, SM_TOTAL + STAMP_EXTRA);
  }
  CUtensorMap tm;
  cuuint64_t gd[2] = {(cuuint64_t)DIM, (cuuint64_t)SEQ}; cuuint64_t gs[1] = {(cuuint64_t)DIM * 2};
  cuuint32_t bd[2] = {8, 256}; cuuint32_t es[2] = {1, 1};
  enc(&tm, CU_TENSOR_MAP_DATA_TYPE_BFLOAT16, 2, d_in[0], gd, gs, bd, es, CU_TENSOR_MAP_INTERLEAVE_NONE,
      CU_TENSOR_MAP_SWIZZLE_NONE, CU_TENSOR_MAP_L2_PROMOTION_L2_128B, CU_TENSOR_MAP_FLOAT_OOB_FILL_NONE);
  CUtensorMap to;
  cuuint32_t bo[2] = {8, 128};
  enc(&to, CU_TENSOR_MAP_DATA_TYPE_BFLOAT16, 2, d_out, gd, gs, bo, es, CU_TENSOR_MAP_INTERLEAVE_NONE,
      CU_TENSOR_MAP_SWIZZLE_NONE, CU_TENSOR_MAP_L2_PROMOTION_NONE, CU_TENSOR_MAP_FLOAT_OOB_FILL_NONE);
  Params P;
  typedef const __nv_bfloat16* bp;
  P.u = (bp)d_in[0];
  const int mi[10] = {1, 2, 5, 6, 10, 11, 12, 13, 3, 4}, vi[4] = {7, 14, 8, 15};
  for (int i = 0; i < 10; i++) P.pm[i] = (bp)d_in[mi[i]];
  for (int i = 0; i < 4; i++) P.pv[i] = (bp)d_in[vi[i]];
  P.gate_w = (bp)d_in[16];
  P.out = (__nv_bfloat16*)d_out;
  ssm_gated_kernel<<<NCTA, NTHR, SM_TOTAL + STAMP_EXTRA, cudaStreamPerThread>>>(tm, to, P);
}
```

```cpp
#include <cuda_runtime.h>
#include <cuda_bf16.h>
#include <cuda_fp16.h>
#include <cuda.h>
#include <stdint.h>

#define STAMP(i) __syncwarp()
#define STAMP_EXTRA 0
#define STAMP_DUMP() do {} while (0)

namespace {

constexpr int SEQ = 2048, DIM = 512, NMODE = 128;
constexpr int NCTA = 128, NTHR = 768;

constexpr int GSLOT   = 3584;
constexpr int GBUF    = 16 * GSLOT;
constexpr int Y2_OFF = 128 * 4, Y3_OFF = (128 + 1536 + 128) * 4, Y_CH = (128 + 1536 + 128 + 1024) * 4;
constexpr int SM_G    = 0;
constexpr int SM_T    = 0;
constexpr int SM_T3   = SM_T + 32768;
constexpr int SM_Y23  = 16 * GSLOT + 1024;
constexpr int SM_RAW  = 2 * GBUF;
constexpr int SM_GW   = SM_RAW, SM_GE = SM_RAW + 10240;
constexpr int XS_CH   = 4 * 512 + 16;
constexpr int SM_XS   = SM_RAW + 16384;
constexpr int UA_ARR  = 74 * 16;
constexpr int UA_CH   = 4 * UA_ARR + 16;
constexpr int SM_RX   = SM_XS + 8320;
constexpr int SM_UA   = SM_RX + 8192;
constexpr int TW_W = 32, TW_X = 576, TW_2 = 656, TW_3 = 736, TW_TOT = 816;
constexpr int TAB_SZ  = TW_TOT * 4;
constexpr int SM_TAB  = SM_UA + 4 * UA_CH;
constexpr int SM_Y01  = SM_TAB + 8 * TAB_SZ;
constexpr int SM_ROW  = SM_Y01;
constexpr int SM_PRM  = SM_Y01 + 2 * Y_CH;
constexpr int SM_MX   = SM_PRM + 10240 + 64;
constexpr int SM_BAR  = SM_MX + 128;
constexpr int SM_TOTAL = SM_BAR + 256;
constexpr int MB_PRM = 0, MB_U = 8, MB_PEER = 16, MB_URDY = 24, MB_ROW = 32, MB_G1 = 40, MB_GW = 48, MB_G23 = 56, MB_Y = 64  , MB_LOC = 96, MB_RX = 160;
static_assert(SM_TOTAL + STAMP_EXTRA <= 232448, "smem");
static_assert(1024 + Y_CH <= 8 * GSLOT && SM_T3 + 16384 <= GBUF, "alias");
static_assert(SM_UA % 128 == 0 && SM_XS % 128 == 0 && SM_TAB % 16 == 0 && SM_Y01 % 16 == 0 && Y_CH % 16 == 0 && SM_T % 128 == 0, "align");

__device__ uint32_t g_gate[SEQ];
__device__ uint32_t g_epoch[NCTA];

struct Params {
  const __nv_bfloat16* u;
  const __nv_bfloat16* pm[10];
  const __nv_bfloat16* pv[4];
  const __nv_bfloat16* gate_w;
  __nv_bfloat16* out;
};

__device__ __forceinline__ void wgmma_n32(float* d, const uint32_t* a, uint64_t desc) {
  asm volatile("wgmma.mma_async.sync.aligned.m64n32k16.f32.bf16.bf16 {%0, %1, %2, %3, %4, %5, %6, %7, %8, %9, %10, %11, %12, %13, %14, %15}, {%16, %17, %18, %19}, %20, 1, 1, 1, 0;\n"
    : "+f"(d[0]), "+f"(d[1]), "+f"(d[2]), "+f"(d[3]), "+f"(d[4]), "+f"(d[5]), "+f"(d[6]), "+f"(d[7]), "+f"(d[8]), "+f"(d[9]), "+f"(d[10]), "+f"(d[11]), "+f"(d[12]), "+f"(d[13]), "+f"(d[14]), "+f"(d[15])
    : "r"(a[0]), "r"(a[1]), "r"(a[2]), "r"(a[3]), "l"(desc));
}

__device__ __forceinline__ void wgmma_n40(float* d, const uint32_t* a, uint64_t desc) {
  asm volatile("wgmma.mma_async.sync.aligned.m64n40k16.f32.bf16.bf16 {%0, %1, %2, %3, %4, %5, %6, %7, %8, %9, %10, %11, %12, %13, %14, %15, %16, %17, %18, %19}, {%20, %21, %22, %23}, %24, 1, 1, 1, 0;\n"
    : "+f"(d[0]), "+f"(d[1]), "+f"(d[2]), "+f"(d[3]), "+f"(d[4]), "+f"(d[5]), "+f"(d[6]), "+f"(d[7]), "+f"(d[8]), "+f"(d[9]), "+f"(d[10]), "+f"(d[11]), "+f"(d[12]), "+f"(d[13]), "+f"(d[14]), "+f"(d[15]), "+f"(d[16]), "+f"(d[17]), "+f"(d[18]), "+f"(d[19])
    : "r"(a[0]), "r"(a[1]), "r"(a[2]), "r"(a[3]), "l"(desc));
}

__device__ __forceinline__ void wgmma_n48(float* d, const uint32_t* a, uint64_t desc) {
  asm volatile("wgmma.mma_async.sync.aligned.m64n48k16.f32.bf16.bf16 {%0, %1, %2, %3, %4, %5, %6, %7, %8, %9, %10, %11, %12, %13, %14, %15, %16, %17, %18, %19, %20, %21, %22, %23}, {%24, %25, %26, %27}, %28, 1, 1, 1, 0;\n"
    : "+f"(d[0]), "+f"(d[1]), "+f"(d[2]), "+f"(d[3]), "+f"(d[4]), "+f"(d[5]), "+f"(d[6]), "+f"(d[7]), "+f"(d[8]), "+f"(d[9]), "+f"(d[10]), "+f"(d[11]), "+f"(d[12]), "+f"(d[13]), "+f"(d[14]), "+f"(d[15]), "+f"(d[16]), "+f"(d[17]), "+f"(d[18]), "+f"(d[19]), "+f"(d[20]), "+f"(d[21]), "+f"(d[22]), "+f"(d[23])
    : "r"(a[0]), "r"(a[1]), "r"(a[2]), "r"(a[3]), "l"(desc));
}

__device__ __forceinline__ void wgmma_n56(float* d, const uint32_t* a, uint64_t desc) {
  asm volatile("wgmma.mma_async.sync.aligned.m64n56k16.f32.bf16.bf16 {%0, %1, %2, %3, %4, %5, %6, %7, %8, %9, %10, %11, %12, %13, %14, %15, %16, %17, %18, %19, %20, %21, %22, %23, %24, %25, %26, %27}, {%28, %29, %30, %31}, %32, 1, 1, 1, 0;\n"
    : "+f"(d[0]), "+f"(d[1]), "+f"(d[2]), "+f"(d[3]), "+f"(d[4]), "+f"(d[5]), "+f"(d[6]), "+f"(d[7]), "+f"(d[8]), "+f"(d[9]), "+f"(d[10]), "+f"(d[11]), "+f"(d[12]), "+f"(d[13]), "+f"(d[14]), "+f"(d[15]), "+f"(d[16]), "+f"(d[17]), "+f"(d[18]), "+f"(d[19]), "+f"(d[20]), "+f"(d[21]), "+f"(d[22]), "+f"(d[23]), "+f"(d[24]), "+f"(d[25]), "+f"(d[26]), "+f"(d[27])
    : "r"(a[0]), "r"(a[1]), "r"(a[2]), "r"(a[3]), "l"(desc));
}

__device__ __forceinline__ void wgmma_n64(float* d, const uint32_t* a, uint64_t desc) {
  asm volatile("wgmma.mma_async.sync.aligned.m64n64k16.f32.bf16.bf16 {%0, %1, %2, %3, %4, %5, %6, %7, %8, %9, %10, %11, %12, %13, %14, %15, %16, %17, %18, %19, %20, %21, %22, %23, %24, %25, %26, %27, %28, %29, %30, %31}, {%32, %33, %34, %35}, %36, 1, 1, 1, 0;\n"
    : "+f"(d[0]), "+f"(d[1]), "+f"(d[2]), "+f"(d[3]), "+f"(d[4]), "+f"(d[5]), "+f"(d[6]), "+f"(d[7]), "+f"(d[8]), "+f"(d[9]), "+f"(d[10]), "+f"(d[11]), "+f"(d[12]), "+f"(d[13]), "+f"(d[14]), "+f"(d[15]), "+f"(d[16]), "+f"(d[17]), "+f"(d[18]), "+f"(d[19]), "+f"(d[20]), "+f"(d[21]), "+f"(d[22]), "+f"(d[23]), "+f"(d[24]), "+f"(d[25]), "+f"(d[26]), "+f"(d[27]), "+f"(d[28]), "+f"(d[29]), "+f"(d[30]), "+f"(d[31])
    : "r"(a[0]), "r"(a[1]), "r"(a[2]), "r"(a[3]), "l"(desc));
}

__device__ __forceinline__ uint32_t smem_u32(const void* p) { return (uint32_t)__cvta_generic_to_shared(p); }
__device__ __forceinline__ uint64_t mkdesc(uint32_t addr, uint32_t lbo, uint32_t sbo) {
  return (uint64_t)((addr & 0x3FFFF) >> 4) | ((uint64_t)(lbo >> 4) << 16) | ((uint64_t)(sbo >> 4) << 32);
}
__device__ __forceinline__ uint32_t lds32(uint32_t a) { uint32_t v; asm volatile("ld.shared.u32 %0, [%1];" : "=r"(v) : "r"(a) : "memory"); return v; }
__device__ __forceinline__ uint4 lds128(uint32_t a) { uint4 v; asm volatile("ld.shared.v4.u32 {%0,%1,%2,%3}, [%4];" : "=r"(v.x), "=r"(v.y), "=r"(v.z), "=r"(v.w) : "r"(a) : "memory"); return v; }
__device__ __forceinline__ float ldsbf(uint32_t a) { uint16_t v; asm volatile("ld.shared.u16 %0, [%1];" : "=h"(v) : "r"(a) : "memory"); return __uint_as_float((uint32_t)v << 16); }
__device__ __forceinline__ void sts16(uint32_t a, uint32_t v) { asm volatile("st.shared.u16 [%0], %1;" :: "r"(a), "h"((uint16_t)v) : "memory"); }
__device__ __forceinline__ void sts32(uint32_t a, uint32_t v) { asm volatile("st.shared.u32 [%0], %1;" :: "r"(a), "r"(v) : "memory"); }
__device__ __forceinline__ void sts128(uint32_t a, uint32_t x, uint32_t y, uint32_t z, uint32_t w) { asm volatile("st.shared.v4.u32 [%0], {%1,%2,%3,%4};" :: "r"(a), "r"(x), "r"(y), "r"(z), "r"(w) : "memory"); }
__device__ __forceinline__ void ldsm4t(uint32_t a, uint32_t* r) {
  asm volatile("ldmatrix.sync.aligned.m8n8.x4.trans.shared.b16 {%0,%1,%2,%3}, [%4];" : "=r"(r[0]), "=r"(r[1]), "=r"(r[2]), "=r"(r[3]) : "r"(a) : "memory");
}
__device__ __forceinline__ void mma_f16(float* c, const uint32_t* a, const uint32_t* b) {
  asm volatile("mma.sync.aligned.m16n8k16.row.col.f32.f16.f16.f32 {%0,%1,%2,%3}, {%4,%5,%6,%7}, {%8,%9}, {%0,%1,%2,%3};"
    : "+f"(c[0]), "+f"(c[1]), "+f"(c[2]), "+f"(c[3]) : "r"(a[0]), "r"(a[1]), "r"(a[2]), "r"(a[3]), "r"(b[0]), "r"(b[1]));
}
__device__ __forceinline__ void stsm4(uint32_t a, const uint32_t* r) {
  asm volatile("stmatrix.sync.aligned.m8n8.x4.shared.b16 [%0], {%1,%2,%3,%4};" :: "r"(a), "r"(r[0]), "r"(r[1]), "r"(r[2]), "r"(r[3]) : "memory");
}
__device__ __forceinline__ void stsm4t(uint32_t a, const uint32_t* r) {
  asm volatile("stmatrix.sync.aligned.m8n8.x4.trans.shared.b16 [%0], {%1,%2,%3,%4};" :: "r"(a), "r"(r[0]), "r"(r[1]), "r"(r[2]), "r"(r[3]) : "memory");
}
__device__ __forceinline__ void mma_bf16(float* c, uint32_t a0, uint32_t a1, uint32_t a2, uint32_t a3, const uint32_t* b) {
  asm volatile("mma.sync.aligned.m16n8k16.row.col.f32.bf16.bf16.f32 {%0,%1,%2,%3}, {%4,%5,%6,%7}, {%8,%9}, {%0,%1,%2,%3};"
    : "+f"(c[0]), "+f"(c[1]), "+f"(c[2]), "+f"(c[3]) : "r"(a0), "r"(a1), "r"(a2), "r"(a3), "r"(b[0]), "r"(b[1]));
}
__device__ __forceinline__ void bar_sync(int id, int n) { asm volatile("bar.sync %0, %1;" :: "r"(id), "r"(n) : "memory"); }
__device__ __forceinline__ void bar_arrive(int id, int n) { asm volatile("bar.arrive %0, %1;" :: "r"(id), "r"(n) : "memory"); }
__device__ __forceinline__ float ex2f(float x) { float y; asm("ex2.approx.ftz.f32 %0, %1;" : "=f"(y) : "f"(x)); return y; }
__device__ __forceinline__ float sinaf(float x) { float y; asm("sin.approx.ftz.f32 %0, %1;" : "=f"(y) : "f"(x)); return y; }
__device__ __forceinline__ float cosaf(float x) { float y; asm("cos.approx.ftz.f32 %0, %1;" : "=f"(y) : "f"(x)); return y; }
__device__ __forceinline__ uint32_t pack_h2(float lo, float hi) { uint32_t r; asm("cvt.rn.f16x2.f32 %0, %1, %2;" : "=r"(r) : "f"(hi), "f"(lo)); return r; }
__device__ __forceinline__ uint32_t pack_bf2(float lo, float hi) { uint32_t r; asm("cvt.rn.bf16x2.f32 %0, %1, %2;" : "=r"(r) : "f"(hi), "f"(lo)); return r; }
__device__ __forceinline__ float bf_lo(uint32_t v) { return __uint_as_float(v << 16); }
__device__ __forceinline__ float bf_hi(uint32_t v) { return __uint_as_float(v & 0xffff0000u); }
__device__ __forceinline__ float bf16_round(float x) { return __bfloat162float(__float2bfloat16_rn(x)); }
__device__ __forceinline__ uint32_t hadd(uint32_t a, uint32_t b) { __nv_bfloat162 r = __hadd2(*(__nv_bfloat162*)&a, *(__nv_bfloat162*)&b); return *(uint32_t*)&r; }
__device__ __forceinline__ float exp_acc(float x) {
  const float L = 1.4426950408889634f, Ll = 1.9259629911266175e-8f;
  float t = x * L, r = fmaf(x, L, -t); r = fmaf(x, Ll, r);
  return ex2f(t) * fmaf(r, 0.6931471805599453f, 1.f);
}
__device__ __forceinline__ void mbar_init(uint32_t a, int n) { asm volatile("mbarrier.init.shared.b64 [%0], %1;" :: "r"(a), "r"(n)); }
__device__ __forceinline__ void mbar_arrive(uint32_t a) { asm volatile("mbarrier.arrive.shared.b64 _, [%0];" :: "r"(a) : "memory"); }
__device__ __forceinline__ void mbar_expect(uint32_t a, int bytes) { asm volatile("mbarrier.arrive.expect_tx.shared.b64 _, [%0], %1;" :: "r"(a), "r"(bytes) : "memory"); }
__device__ __forceinline__ void mbar_wait(uint32_t a) {
  uint32_t ok = 0; int it = 0;
  while (!ok && it++ < (1 << 20))
    asm volatile("{ .reg .pred p; mbarrier.try_wait.parity.shared.b64 p, [%1], 0, 2000; selp.u32 %0, 1, 0, p; }" : "=r"(ok) : "r"(a) : "memory");
}
__device__ __forceinline__ void warp_arrive(uint32_t a, int lane) { __syncwarp(); if (lane == 0) mbar_arrive(a); }
__device__ __forceinline__ void fence_async() { asm volatile("fence.proxy.async.shared::cta;" ::: "memory"); }
__device__ __forceinline__ uint32_t mapa(uint32_t a, uint32_t rank) { uint32_t r; asm("mapa.shared::cluster.u32 %0, %1, %2;" : "=r"(r) : "r"(a), "r"(rank)); return r; }
__device__ __forceinline__ void dsmem_copy(uint32_t dst, uint32_t src, int bytes, uint32_t mb) {
  asm volatile("cp.async.bulk.shared::cluster.shared::cta.mbarrier::complete_tx::bytes [%0], [%1], %2, [%3];" :: "r"(dst), "r"(src), "r"(bytes), "r"(mb) : "memory");
}
__device__ __forceinline__ void bulk_g2s(uint32_t dst, const void* src, int bytes, uint32_t mb) {
  asm volatile("cp.async.bulk.shared::cluster.global.mbarrier::complete_tx::bytes [%0], [%1], %2, [%3];" :: "r"(dst), "l"(src), "r"(bytes), "r"(mb) : "memory");
}
__device__ __forceinline__ void wg_fence() { asm volatile("wgmma.fence.sync.aligned;" ::: "memory"); }
__device__ __forceinline__ void wg_commit() { asm volatile("wgmma.commit_group.sync.aligned;" ::: "memory"); }
template <int N> __device__ __forceinline__ void wg_wait() { asm volatile("wgmma.wait_group.sync.aligned %0;" :: "n"(N) : "memory"); }
template <int N> __device__ __forceinline__ void fence_acc(float* d) {
  #pragma unroll
  for (int i = 0; i < N; i++) asm volatile("" : "+f"(d[i]) :: "memory");
}

struct cf { float x, y; };
__device__ __forceinline__ cf cmul(cf a, cf b) { cf r; r.x = a.x * b.x - a.y * b.y; r.y = a.x * b.y + a.y * b.x; return r; }
__device__ __forceinline__ cf cmulc(cf a, cf b) { cf r; r.x = a.x * b.x + a.y * b.y; r.y = a.y * b.x - a.x * b.y; return r; }
__device__ __forceinline__ cf csq(cf a) { cf r; r.x = a.x * a.x - a.y * a.y; r.y = (a.x + a.x) * a.y; return r; }
__device__ __forceinline__ cf cexp_fast(float a2, float th, float x) {
  float e = ex2f(a2 * x), ph = th * x; cf r; r.x = e * cosaf(ph); r.y = e * sinaf(ph); return r;
}
struct hp { uint32_t r, i; };
__device__ __forceinline__ hp hbro(cf m) { hp h; h.r = pack_h2(m.x, m.x); h.i = pack_h2(m.y, m.y); return h; }
template <bool CONJ> __device__ __forceinline__ hp hmul(hp a, hp m) {
  const __half2 ar = *(__half2*)&a.r, ai = *(__half2*)&a.i, mr = *(__half2*)&m.r, mi = CONJ ? __hneg2(*(__half2*)&m.i) : *(__half2*)&m.i;
  const __half2 x = __hfma2(ar, mr, __hneg2(__hmul2(ai, mi))), y = __hfma2(ar, mi, __hmul2(ai, mr));
  hp o; o.r = *(uint32_t*)&x; o.i = *(uint32_t*)&y; return o;
}
__device__ __forceinline__ hp hlo(hp a, hp b) { hp o; o.r = __byte_perm(a.r, b.r, 0x5410); o.i = __byte_perm(a.i, b.i, 0x5410); return o; }
__device__ __forceinline__ void put4(uint32_t a, hp p0, hp p1, hp p2, hp p3) {
  sts128(a, p0.r, p1.r, p2.r, p3.r); sts128(a + 128, p0.i, p1.i, p2.i, p3.i);
}

struct Pow { hp t0, z, m2, m4, m256, m512, m1024, b0, m16, m32; uint32_t m64, m128; };
__device__ __forceinline__ void gen_powers(Pow& p, float al, float tt, cf c) {
  const cf w1 = cexp_fast(al, tt, 1.f), w64 = cexp_fast(al, tt, 64.f);
  const cf w2 = csq(w1), w4 = csq(w2), w8 = csq(w4), w16 = csq(w8), w32 = csq(w16);
  const cf w128 = csq(w64), w256 = csq(w128), w512 = csq(w256), w1024 = csq(w512);
  const cf c1 = cmulc(c, w1), c512 = cmulc(c, w512), c768 = cmulc(c512, w256);
  p.t0.r = pack_h2(c.x, c1.x); p.t0.i = pack_h2(c.y, c1.y);
  p.z.r = pack_h2(c512.x, c768.x); p.z.i = pack_h2(c512.y, c768.y);
  p.m2 = hbro(w2); p.m4 = hbro(w4); p.m256 = hbro(w256); p.m512 = hbro(w512); p.m1024 = hbro(w1024);
  p.b0.r = pack_h2(1.f, w8.x); p.b0.i = pack_h2(0.f, w8.y);
  p.m16 = hbro(w16); p.m32 = hbro(w32); p.m64 = pack_h2(w64.x, w64.y); p.m128 = pack_h2(w128.x, w128.y);
}
constexpr int KSLOT = 1024;
__device__ __forceinline__ void gen_store(const Pow& p, uint32_t gb, uint32_t gm) {
  const uint32_t bb = gb + 256;
  hp t1 = hmul<true>(p.t0, p.m2), t2 = hmul<true>(p.t0, p.m4), t3 = hmul<true>(t1, p.m4);
  put4(bb, p.t0, t1, t2, t3);
  const hp z4 = hmul<true>(p.z, p.m4);
  hp u0, u1; u0.r = __byte_perm(p.z.r, z4.r, 0x5410); u0.i = __byte_perm(p.z.i, z4.i, 0x5410);
  u1.r = __byte_perm(p.z.r, z4.r, 0x7632); u1.i = __byte_perm(p.z.i, z4.i, 0x7632);
  put4(bb + 256, hmul<true>(hlo(p.t0, t1), p.m256), hmul<true>(hlo(t2, t3), p.m256), u0, u1);
  u0 = hmul<true>(p.z, p.m512); u1 = hmul<true>(p.z, p.m1024);
  const hp u2 = hmul<true>(u0, p.m1024);
  put4(bb + 512, u0, u1, u2, u2);
  t1 = hmul<false>(p.b0, p.m16); t2 = hmul<false>(p.b0, p.m32); t3 = hmul<false>(t1, p.m32);
  put4(gb, p.b0, t1, t2, t3);
  sts16(gm, p.m64); sts16(gm + 4, p.m64 >> 16); sts16(gm + 128, p.m128); sts16(gm + 132, p.m128 >> 16);
  __syncwarp();
}
__device__ __forceinline__ void gen_contract(float* d, uint32_t la, uint32_t lb, uint32_t lm, uint32_t zr) {
  #pragma unroll
  for (int ks = 0; ks < 4; ks++) {
    uint32_t fa[4], fc[4], fb[8];
    ldsm4t(la + ks * KSLOT, fb + 4);
    hp m64, m128, x, y;
    asm volatile("ld.shared.v2.u32 {%0,%1}, [%2];" : "=r"(m64.r), "=r"(m64.i) : "r"(lm + ks * 32) : "memory");
    asm volatile("ld.shared.v2.u32 {%0,%1}, [%2];" : "=r"(m128.r), "=r"(m128.i) : "r"(lm + ks * 32 + 128) : "memory");
    ldsm4t(lb + ks * KSLOT, fb);
    x.r = fb[6]; x.i = fb[7]; y = hmul<false>(x, m64);
    fa[0] = x.r + zr; fa[2] = x.i + zr; fa[1] = y.r; fa[3] = y.i;
    x = hmul<false>(x, m128); y = hmul<false>(y, m128);
    fc[0] = x.r; fc[2] = x.i; fc[1] = y.r; fc[3] = y.i;
    #pragma unroll
    for (int nt = 0; nt < 3; nt++) { mma_f16(d + 4 * nt, fa, fb + 2 * nt); mma_f16(d + 12 + 4 * nt, fc, fb + 2 * nt); }
  }
  __syncwarp();
}

template <int S> __device__ __forceinline__ void near_step(float* d, uint64_t ud, const uint32_t* a) {
  constexpr int arr = (S & 1) ? 0 : 2;
  constexpr int slot = (S & 1) ? (S - 1) / 2 : S / 2;
  const uint64_t desc = ud + (uint64_t)((arr * UA_ARR + slot * 16) >> 4);
  if constexpr (S < 16) wgmma_n64(d, a, desc);
  else if constexpr (S < 32) wgmma_n56(d, a, desc);
  else if constexpr (S < 34) wgmma_n48(d, a, desc);
  else if constexpr (S == 63) wgmma_n40(d, a, desc);
  else wgmma_n32(d, a, desc);
}
template <int S0, int NS> __device__ __forceinline__ void near_load(uint32_t (*a)[4], uint32_t wa, uint32_t zr) {
  a[0][2] = lds32(wa + (uint32_t)((2 * S0 - 1) * 32));
  #pragma unroll
  for (int i = 0; i < NS; i++) {
    a[i][0] = lds32(wa + (2 * (S0 + i)) * 32);
    a[i][1] = lds32(wa + (2 * (S0 + i) + 1) * 32);
  }
  #pragma unroll
  for (int i = 0; i < NS; i++) {
    a[i][3] = a[i][0] + zr;
    if (i + 1 < NS) a[i + 1][2] = a[i][1] + zr;
  }
}
template <int S0, int NS> __device__ __forceinline__ void near_issue(float* d, uint64_t ua, uint32_t (*a)[4]) {
  wg_fence();
  near_step<S0>(d, ua, a[0]);
  if constexpr (NS > 1) near_step<S0 + 1>(d, ua, a[1]);
  if constexpr (NS > 2) near_step<S0 + 2>(d, ua, a[2]);
  if constexpr (NS > 3) near_step<S0 + 3>(d, ua, a[3]);
  if constexpr (NS > 4) near_step<S0 + 4>(d, ua, a[4]);
  if constexpr (NS > 5) near_step<S0 + 5>(d, ua, a[5]);
  wg_commit();
}

__device__ __forceinline__ void sts2x(uint32_t o, const uint32_t* w) {
  const bool sw = (threadIdx.x >> 2) & 1;
  sts128(o + (sw ? 16 : 0), sw ? w[4] : w[0], sw ? w[5] : w[1], sw ? w[6] : w[2], sw ? w[7] : w[3]);
  sts128(o + (sw ? 0 : 16), sw ? w[0] : w[4], sw ? w[1] : w[5], sw ? w[2] : w[6], sw ? w[3] : w[7]);
}
__device__ __forceinline__ void ytab_chunk(uint32_t ub, uint32_t yb, int chi) {
  auto ca = [&](int c) { return ub + (c & 3) * UA_ARR - (c >> 2) * 16; };
  const uint4 z = lds128(ca(chi - 2)), a = lds128(ca(chi - 1)), b = lds128(ca(chi)), c = lds128(ca(chi + 1));
  const float v[23] = {bf_hi(z.z), bf_lo(z.w), bf_hi(z.w),
                       bf_lo(a.x), bf_hi(a.x), bf_lo(a.y), bf_hi(a.y), bf_lo(a.z), bf_hi(a.z), bf_lo(a.w), bf_hi(a.w),
                       bf_lo(b.x), bf_hi(b.x), bf_lo(b.y), bf_hi(b.y), bf_lo(b.z), bf_hi(b.z), bf_lo(b.w), bf_hi(b.w),
                       bf_lo(c.x), bf_hi(c.x), bf_lo(c.y), bf_hi(c.y)};
  float s[24];
  s[13] = 0.f; s[14] = v[13]; s[12] = -v[12];
  #pragma unroll
  for (int i = 15; i < 24; i++) s[i] = s[i - 1] + v[i - 1];
  #pragma unroll
  for (int i = 11; i >= 0; i--) s[i] = s[i + 1] - v[i];
  uint32_t w[8];
  {
    #pragma unroll
    for (int i = 0; i < 8; i++) w[i] = pack_bf2(s[i + 14] - s[i + 9], s[i + 9] - s[i + 6]);
    const int cp = (chi ^ ((chi >> 2) & 1)) * 32;
    uint32_t o = yb + Y2_OFF + cp;
    sts2x(o, w);
    if (chi < 128) {
      #pragma unroll
      for (int i = 0; i < 8; i++) w[i] = pack_bf2(s[i + 16] - s[i + 7], s[i + 7] - s[i]);
      o = yb + Y3_OFF + cp;
      sts2x(o, w);
    }
  }
}

__device__ __forceinline__ uint32_t ldv32(uint32_t a) { uint32_t v; asm volatile("ld.volatile.shared.u32 %0, [%1];" : "=r"(v) : "r"(a) : "memory"); return v; }
__device__ __forceinline__ void ld_frag(uint32_t* n, uint32_t x, int dp, int dm) { n[0] = ldv32(x); n[1] = ldv32(x + dp); n[2] = ldv32(x + dm); }
__device__ __forceinline__ void far_octet(float (*acc)[4], int j0, uint32_t yb, uint32_t kb, int g, int q, const uint32_t (*b2)[2]) {
  const int mu = g >> 1;
  const uint32_t zr = ldv32(kb);
  uint32_t a[4][4];
  const int dp = q < 2 ? -32 : 32;
  if (j0 >= 4) {
    const uint32_t ya = yb + Y2_OFF + (64 * (j0 - 8) + 48 - 16 * q + (q < 2 ? 8 : 0) + g) * 4;
    const int dm = (q == 0) ? -96 : (q == 2) ? -32 : -64;
    #pragma unroll
    for (int i = 0; i < 3; i++) ld_frag(a[i], ya + (3 - i) * 256, dp, dm);
    #pragma unroll
    for (int i = 0; i < 12; i++) {
      const int br = 3 - i;
      if ((i & 3) == 1 && j0 + br < 7) break;
      if (i + 3 < 12) ld_frag(a[(i + 3) & 3], ya + (br - 3) * 256, dp, dm);
      uint32_t* c = a[i & 3];
      c[3] = c[0] + zr;
      #pragma unroll
      for (int j = 0; j < 4; j++) { const int s = j - br; if (s >= 0 && s < 9) mma_bf16(acc[j], c[0], c[1], c[2], c[3], b2[s]); }
    }
  }
  if (j0 >= 12) {
    const uint32_t ya = yb + Y3_OFF + (64 * (j0 - 16) + 48 - 16 * q + (q < 2 ? 8 : 0) + g) * 4;
    #pragma unroll
    for (int i = 0; i < 3; i++) { a[i][0] = ldv32(ya + (3 - i) * 256); a[i][1] = ldv32(ya + (3 - i) * 256 + dp); }
    uint32_t b3[9][2];
    #pragma unroll
    for (int s = 0; s < 9; s++) { b3[s][0] = ldv32(kb + (TW_3 + mu + q + 8 * s) * 4); b3[s][1] = ldv32(kb + (TW_3 + mu + q + 8 * s + 4) * 4); }
    #pragma unroll
    for (int i = 0; i < 17; i++) {
      const int br = 3 - i;
      if ((i & 3) == 1 && j0 + br < 15) break;
      if (i + 3 < 18) { uint32_t* n = a[(i + 3) & 3]; n[0] = ldv32(ya + (br - 3) * 256); n[1] = ldv32(ya + (br - 3) * 256 + dp); }
      uint32_t* c = a[i & 3];
      c[2] = a[(i + 1) & 3][0] + zr; c[3] = a[(i + 1) & 3][1] + zr;
      #pragma unroll
      for (int j = 0; j < 4; j++) { const int s2 = j - br; if (s2 >= 0 && !(s2 & 1)) mma_bf16(acc[j], c[0], c[1], c[2], c[3], b3[s2 >> 1]); }
    }
  }
}

__global__ void __cluster_dims__(2, 1, 1) __launch_bounds__(NTHR, 1)
ssm_gated_kernel(const __grid_constant__ CUtensorMap tmap_u, const __grid_constant__ CUtensorMap tmap_o, const __grid_constant__ Params P) {
  extern __shared__ __align__(1024) unsigned char smem[];
  const uint32_t sb = smem_u32(smem);
  const int tid = threadIdx.x, warp = __shfl_sync(~0u, tid >> 5, 0), lane = tid & 31;
  const int g = lane >> 2, q = lane & 3;
  const int cta = blockIdx.x, c0 = cta * 4, rank = cta & 1;
  const uint32_t mb = sb + SM_BAR;
  if (tid == 0) {
    mbar_init(mb + MB_PRM, 1); mbar_init(mb + MB_ROW, 1);
    fence_async();
    mbar_expect(mb + MB_PRM, 10240 + 64);
    #pragma unroll
    for (int i = 0; i < 10; i++) bulk_g2s(sb + SM_PRM + i * 1024, P.pm[i] + c0 * NMODE, 1024, mb + MB_PRM);
    #pragma unroll
    for (int i = 0; i < 4; i++) bulk_g2s(sb + SM_PRM + 10240 + i * 16, P.pv[i] + (cta >> 1) * 8, 16, mb + MB_PRM);
  }
  if (tid == 32) {
    mbar_init(mb + MB_U, 1); mbar_init(mb + MB_URDY, 1);
    mbar_init(mb + MB_G1, 8); mbar_init(mb + MB_G23, 8); mbar_init(mb + MB_PEER, 1); mbar_init(mb + MB_GW, 4);
    #pragma unroll
    for (int i = 0; i < 4; i++) mbar_init(mb + MB_Y + 8 * i, 8);
    #pragma unroll
    for (int i = 0; i < 8; i++) { mbar_init(mb + MB_LOC + 8 * i, i ? 20 : 16); mbar_init(mb + MB_RX + 8 * i, 1); }
    asm volatile("fence.mbarrier_init.release.cluster;" ::: "memory");
    fence_async();
  }
  STAMP(0);

  if (warp < 16) {
    const int ch = warp >> 2, br = (warp >> 1) & 1, w0 = warp & 1;
    asm volatile("setmaxnreg.inc.sync.aligned.u32 96;");
    for (int i = tid; i < (SM_Y01 - SM_TAB) / 16; i += 512) sts128(sb + SM_TAB + i * 16, 0, 0, 0, 0);
    if (tid < 160) sts128(sb + SM_UA + (tid / 40) * UA_CH + ((tid / 10) & 3) * UA_ARR + (64 + tid % 10) * 16, 0, 0, 0, 0);
    asm volatile("barrier.cluster.arrive.relaxed.aligned;" ::: "memory");
    bar_sync(0, NTHR);
    const uint32_t tab = sb + SM_TAB + (ch * 2 + br) * TAB_SZ;
    const uint32_t zr = lds32(tab);
    const uint32_t yb = sb + (ch < 2 ? SM_Y01 + ch * Y_CH : SM_Y23 + (ch - 2) * 8 * GSLOT);
    {
      const uint32_t gw = sb + SM_G + warp * (2 * GSLOT);
      const uint32_t gb = gw + (lane >> 3) * KSLOT + (lane & 7) * 16;
      const uint32_t gm = gw + 4 * KSLOT + (lane >> 1) * 8 + (lane & 1) * 2;
      const uint32_t la = gw + (((lane >> 3) * 128 + 768) & 1023) + (lane & 7) * 16;
      const uint32_t lb = gw + 256 + (lane >> 3) * 128 + (lane & 7) * 16;
      const uint32_t lm = gw + 4 * KSLOT + q * 8;
      float a2[2], th[2]; cf cc[2];
      const uint32_t pp = sb + SM_PRM + br * 4096 + ch * 256 + (w0 * 32 + lane) * 2;
      const uint32_t pl = sb + SM_PRM + 10240 + br * 16 + rank * 8 + ch * 2;
      mbar_wait(mb + MB_PRM);
      STAMP(1);
      const float dt = bf16_round(exp_acc(ldsbf(pl)));
      float mxf = 0.f;
      #pragma unroll
      for (int r = 0; r < 2; r++) {
        float are = ldsbf(pp + r * 128);
        if (br) are = -bf16_round(exp_acc(are));
        a2[r] = (are * dt) * 1.4426950408889634f; th[r] = ldsbf(pp + r * 128 + 1024) * dt;
        cf c = {ldsbf(pp + r * 128 + 2048), ldsbf(pp + r * 128 + 3072)}, dB = {dt + dt, 0.f};
        if (!br) { dB.x = dt * ldsbf(pp + r * 128 + 8192); dB.y = dt * ldsbf(pp + r * 128 + 9216); }
        c = cmul(c, dB); cc[r].x = c.x; cc[r].y = -c.y;
        mxf = fmaxf(mxf, fmaxf(fabsf(c.x), fabsf(c.y)));
      }
      const int e = min(max((int)(__reduce_max_sync(~0u, __float_as_uint(mxf)) >> 23), 1), 252);
      const float sc = __uint_as_float((uint32_t)(253 - e) << 23);
      float d[24];
      #pragma unroll
      for (int i = 0; i < 24; i++) d[i] = 0.f;
      {
        Pow p;
        cf c = cc[0]; c.x *= sc; c.y *= sc;
        gen_powers(p, a2[0], th[0], c);
        if (ch >= 2) bar_sync(5, 512);
        gen_store(p, gb, gm);
        if (ch < 2) bar_arrive(5, 512);
        STAMP(2);
        c = cc[1]; c.x *= sc; c.y *= sc;
        gen_powers(p, a2[1], th[1], c);
        gen_contract(d, la, lb, lm, zr);
        gen_store(p, gb, gm);
        STAMP(3);
        gen_contract(d, la, lb, lm, zr);
      }
      const float isc = __uint_as_float((uint32_t)(e + 1) << 23);
      const int jr = w0 * 16 + g;
      const uint32_t a0 = tab + (TW_W + 8 * jr + 2 * q) * 4;
      const uint32_t a1 = tab + (q < 2 ? TW_W + 256 + 8 * jr + 4 * q : TW_2 + 6 + 32 * (q - 2) + jr) * 4;
      const uint32_t a3 = tab + TW_3 * 4 + (6 + 64 * q + jr) * 2;
      float k[12];
      {
        #pragma unroll
        for (int i = 0; i < 3; i++) {
          sts128(gw + i * 512 + lane * 16, __float_as_uint((w0 ? d[4 * i] : d[12 + 4 * i]) * isc), __float_as_uint((w0 ? d[4 * i + 1] : d[13 + 4 * i]) * isc),
                 __float_as_uint((w0 ? d[4 * i + 2] : d[14 + 4 * i]) * isc), __float_as_uint((w0 ? d[4 * i + 3] : d[15 + 4 * i]) * isc));
        }
        const float own = (lane == 0 ? d[8] : d[4]) * isc;
        if (!w0 && (lane == 0 || lane == 2)) sts32(gw + 1536 + lane * 2, __float_as_uint(own));
        const float fo = __shfl_sync(~0u, own, q == 3 ? 0 : 2);
        bar_sync(1 + ch, 128);
        const uint32_t po = sb + SM_G + (warp ^ 1) * (2 * GSLOT) + lane * 16;
        #pragma unroll
        for (int i = 0; i < 3; i++) {
          const uint4 v = lds128(po + i * 512);
          k[4 * i]     = fmaf(w0 ? d[12 + 4 * i] : d[4 * i], isc, __uint_as_float(v.x));
          k[4 * i + 1] = fmaf(w0 ? d[13 + 4 * i] : d[4 * i + 1], isc, __uint_as_float(v.y));
          k[4 * i + 2] = fmaf(w0 ? d[14 + 4 * i] : d[4 * i + 2], isc, __uint_as_float(v.z));
          k[4 * i + 3] = fmaf(w0 ? d[15 + 4 * i] : d[4 * i + 3], isc, __uint_as_float(v.w));
        }
        if (w0 && g == 7 && (q & 1)) k[7] -= fo + __uint_as_float(lds32(po - lane * 16 + 1536 + (q == 3 ? 0 : 4)));
        warp_arrive(mb + (ch < 2 ? MB_G1 : MB_G23), lane);
      }
      if (jr == 0 && q == 0) k[0] += ldsbf(pl + 32);
      #pragma unroll
      for (int h = 0; h < 2; h++) {
        uint32_t w = pack_bf2(k[2 * h + 1], k[2 * h]);
        sts16(a0 + h * 256, w >> 16); sts32(a0 + h * 256 + 4, w); sts16(a0 + h * 256 + 10, w);
        w = pack_bf2(k[4 + 2 * h], k[5 + 2 * h]);
        if (q < 2) {
          const uint32_t a = a1 + h * 256, w0w = __byte_perm(w, w, 0x1010);
          if (h == 0 && jr == 0 && q == 0) sts16(a, w0w); else { sts16(a - 4, w0w); sts32(a, w0w); }
          sts32(a + 4, w0w); sts32(a + 8, __byte_perm(w, w, 0x1032)); sts16(a + 14, w >> 16);
        } else sts32(a1 + h * 32, w);
        w = pack_bf2(k[8 + 2 * h], k[9 + 2 * h]);
        if (q < 2 || (q == 2 && h == 0 && jr == 0)) sts16(a3 + h * 16, w);
        if (q < 2) sts16(a3 + h * 16 + 64, w >> 16);
        if (h == 0 && jr == 0 && q == 0) { sts16(tab + (TW_X + 1019 - 976) * 4, w); sts16(tab + (TW_X + 1020 - 976) * 4 + 2, w); }
      }
      bar_sync(1 + ch, 128);
      STAMP(4);
    }
    {
      const uint64_t ua = mkdesc(sb + SM_UA + ch * UA_CH, UA_ARR, 128);
      const uint32_t wa = tab + (TW_W + 16 * w0 + g - 2 * q - 16) * 4;
      float d[32];
      #pragma unroll
      for (int i = 0; i < 32; i++) d[i] = 0.f;
      uint32_t A[4][4], B[4][4];
      near_load<0, 4>(A, wa, zr);
      near_load<4, 4>(B, wa, zr);
      STAMP(6);
      mbar_wait(mb + MB_URDY);
      STAMP(7);
      fence_acc<32>(d);
      near_issue<0, 4>(d, ua, A);
      near_issue<4, 4>(d, ua, B);   wg_wait<1>();
      near_load<8, 4>(A, wa, zr);   near_issue<8, 4>(d, ua, A);   wg_wait<1>();
      near_load<12, 4>(B, wa, zr);  near_issue<12, 4>(d, ua, B);  wg_wait<1>();
      near_load<16, 4>(A, wa, zr);
      wg_wait<0>();
      fence_acc<32>(d);
      mbar_wait(mb + MB_GW);
      mbar_wait(mb + MB_G1);
      const int m = lane >> 3, tl = 7 - (lane & 7);
      const uint32_t ga = sb + SM_GW + br * 5120 + ((3 - q) * 40 + 16 * w0 + g) * 4;
      const int c16 = 4 * (tl & 3) + 2 * w0 + (m & 1);
      const uint32_t ta = sb + SM_T + (m >> 1) * 4096 + (tl >> 2) * 2048 + (br * 4 + ch) * 256 + ((c16 ^ (tl >> 1) ^ (rank * 4 + ch)) * 16);
      {
        uint32_t r[2];
        #pragma unroll
        for (int h = 0; h < 2; h++) {
          const uint32_t gw = lds32(ga + 8 * h * 4), y = pack_bf2(d[28 + 2 * h], d[29 + 2 * h]);
          const __nv_bfloat162 t2 = __hmul2(*(const __nv_bfloat162*)&y, *(const __nv_bfloat162*)&gw);
          r[h] = *(const uint32_t*)&t2;
        }
        asm volatile("stmatrix.sync.aligned.m8n8.x2.trans.shared.b16 [%0], {%1,%2};" :: "r"(ta), "r"(r[0]), "r"(r[1]) : "memory");
        warp_arrive(mb + MB_LOC, lane);
      }
      fence_acc<28>(d);
      near_issue<16, 4>(d, ua, A);
      near_load<20, 4>(B, wa, zr);  near_issue<20, 4>(d, ua, B);  wg_wait<1>();
      near_load<24, 4>(A, wa, zr);  near_issue<24, 4>(d, ua, A);  wg_wait<1>();
      near_load<28, 4>(B, wa, zr);  near_issue<28, 4>(d, ua, B);  wg_wait<1>();
      near_load<32, 2>(A, wa, zr);  near_issue<32, 2>(d, ua, A);  wg_wait<1>();
      near_load<63, 3>(B, wa - (uint32_t)((976 + TW_W - TW_X) * 4), zr);
      near_issue<63, 1>(d, ua, B);
      near_issue<64, 2>(d, ua, B + 1);
      wg_wait<0>();
      fence_acc<28>(d);
      STAMP(8);
      #pragma unroll
      for (int i = 1; i < 8; i += 2) {
        uint32_t r[4];
        #pragma unroll
        for (int kk = 0; kk < (i < 7 ? 4 : 2); kk++) {
          const int ii = i + (kk >> 1), h = kk & 1;
          const uint32_t gw = lds32(ga + (ii * 160 + 8 * h) * 4);
          const uint32_t y = pack_bf2(d[4 * (7 - ii) + 2 * h], d[4 * (7 - ii) + 2 * h + 1]);
          const __nv_bfloat162 t2 = __hmul2(*(const __nv_bfloat162*)&y, *(const __nv_bfloat162*)&gw);
          r[kk] = *(const uint32_t*)&t2;
        }
        if (i < 7) stsm4t(ta + i * 4096, r);
        else asm volatile("stmatrix.sync.aligned.m8n8.x2.trans.shared.b16 [%0], {%1,%2};" :: "r"(ta + i * 4096 - (m >> 1) * 4096), "r"(r[0]), "r"(r[1]) : "memory");
        __syncwarp();
        if (lane < (i < 7 ? 2 : 1)) mbar_arrive(mb + MB_LOC + 8 * (i + lane));
      }
    }
    STAMP(9);
    {
      const uint32_t kb = sb + SM_TAB + (ch * 2 + (g & 1)) * TAB_SZ;
      uint32_t b2[9][2];
      #pragma unroll
      for (int s = 0; s < 9; s++)
        asm volatile("ld.shared.v2.u32 {%0,%1}, [%2];" : "=r"(b2[s][0]), "=r"(b2[s][1]) : "r"(kb + (TW_2 + 2 * (g >> 1) + 2 * q + 8 * s) * 4) : "memory");
      mbar_wait(mb + MB_Y + 8 * ch);
      STAMP(10);
      const int c32 = lane, c16 = c32 & 15;
      const uint32_t t3a = sb + SM_T3 + (c32 >> 4) * 1024 + ch * 256 + ((c16 ^ (c32 >> 3) ^ (rank * 4 + ch)) * 16);
      #pragma unroll 1
      for (int ps = 0; ps < 2; ps++) {
        const int o4 = (warp + ch) & 3, oc = ps ? o4 + 4 : o4, j0 = 4 * oc;
        if (oc == 0) continue;
        float acc[4][4];
        uint32_t gq[4];
        #pragma unroll
        for (int j = 0; j < 4; j++) {
          gq[j] = lds32(sb + SM_GE + (32 * (j0 + j) + 8 * q + g) * 4);
          acc[j][0] = acc[j][1] = acc[j][2] = acc[j][3] = 0.f;
        }
        far_octet(acc, j0, yb, kb, g, q, b2);
        uint32_t r[4];
        #pragma unroll
        for (int j = 0; j < 4; j++)
          r[j] = pack_bf2(fmaf(bf_lo(gq[j]), acc[j][0] - acc[j][1], acc[j][1]), fmaf(bf_hi(gq[j]), acc[j][2] - acc[j][3], acc[j][3]));
        stsm4t(t3a + oc * 2048, r);
        warp_arrive(mb + MB_LOC + 8 * oc, lane);
        STAMP(11 + ps);
      }
    }
  } else {
    asm volatile("setmaxnreg.dec.sync.aligned.u32 48;");
    const int aw = warp - 16, at = tid - 512;
    const uint32_t epoch = __ldcg(&g_epoch[cta]) + 1u, tag = epoch & 0xffffu;
    asm volatile("barrier.cluster.arrive.relaxed.aligned;" ::: "memory");
    bar_sync(0, NTHR);
    STAMP(1);
    if (aw >= 4) {
      const int bw = aw - 4, bt = at - 128;
      if (bt == 0) {
    mbar_expect(mb + MB_ROW, 16384 + 1024);
    bulk_g2s(sb + SM_ROW, P.u + (size_t)cta * 16 * DIM, 16384, mb + MB_ROW);
    bulk_g2s(sb + SM_ROW + 16384, P.gate_w, 1024, mb + MB_ROW);
        mbar_expect(mb + MB_U, 16384);
        #pragma unroll
        for (int i = 0; i < 4; i++)
          asm volatile("cp.async.bulk.tensor.2d.shared::cluster.global.mbarrier::complete_tx::bytes [%0], [%1, {%3, %4}], [%2];"
                       :: "r"(sb + SM_RAW + i * 4096), "l"((uint64_t)&tmap_u), "r"(mb + MB_U), "r"((cta >> 1) * 8), "r"(rank * 1024 + i * 256) : "memory");
        mbar_expect(mb + MB_PEER, 8192);
        #pragma unroll
        for (int i = 0; i < 8; i++) mbar_expect(mb + MB_RX + 8 * i, 1024);
      }
      mbar_wait(mb + MB_U);
      STAMP(2);
      const int chs = (lane & 7) - rank * 4, m = lane >> 3;
      const uint32_t base = ((unsigned)chs < 4u) ? sb + SM_UA + chs * UA_CH + m * UA_ARR + (63 - rank * 32) * 16
                                                 : sb + SM_XS + 64 + (chs & 3) * XS_CH + m * 512 + 31 * 16;
      #pragma unroll
      for (int hh = 0; hh < 2; hh++) {
        uint32_t r[4][4];
        #pragma unroll
        for (int it = 0; it < 4; it++) ldsm4t(sb + SM_RAW + ((bw * 8 + hh * 4 + it) * 32 + lane) * 16, r[it]);
        #pragma unroll
        for (int it = 0; it < 4; it++) stsm4(base - (bw * 8 + hh * 4 + it) * 16, r[it]);
      }
      fence_async();
      asm volatile("barrier.cluster.wait.aligned;" ::: "memory");
      bar_sync(11, 128);
      if (lane < 4) {
        dsmem_copy(mapa(sb + SM_UA + bw * UA_CH + lane * UA_ARR + (32 - rank * 32) * 16, rank ^ 1),
                   sb + SM_XS + 64 + bw * XS_CH + lane * 512, 512, mapa(mb + MB_PEER, rank ^ 1));
      }
      STAMP(3);
      mbar_wait(mb + MB_PEER);
      if (bt == 0) mbar_arrive(mb + MB_URDY);
      STAMP(4);
    } else {
      mbar_wait(mb + MB_ROW);
      {
        const uint4 gw0 = lds128(sb + SM_ROW + 16384 + lane * 16), gw1 = lds128(sb + SM_ROW + 16384 + 512 + lane * 16);
        float s[4];
        #pragma unroll
        for (int r = 0; r < 4; r++) {
          const uint4 x0 = lds128(sb + SM_ROW + (aw * 4 + r) * 1024 + lane * 16), x1 = lds128(sb + SM_ROW + (aw * 4 + r) * 1024 + 512 + lane * 16);
          const uint32_t xv[8] = {x0.x, x0.y, x0.z, x0.w, x1.x, x1.y, x1.z, x1.w}, wv[8] = {gw0.x, gw0.y, gw0.z, gw0.w, gw1.x, gw1.y, gw1.z, gw1.w};
          float a = 0.f, b = 0.f;
          #pragma unroll
          for (int i = 0; i < 8; i++) {
            __nv_bfloat162 pr2 = __hmul2(*(const __nv_bfloat162*)&xv[i], *(const __nv_bfloat162*)&wv[i]);
            const uint32_t pv = *(uint32_t*)&pr2;
            a += bf_lo(pv); b += bf_hi(pv);
          }
          s[r] = a + b;
        }
        float t0 = (lane & 1) ? s[1] : s[0], t1 = (lane & 1) ? s[3] : s[2];
        t0 += __shfl_xor_sync(~0u, (lane & 1) ? s[0] : s[1], 1); t1 += __shfl_xor_sync(~0u, (lane & 1) ? s[2] : s[3], 1);
        float t = (lane & 2) ? t1 : t0;
        t += __shfl_xor_sync(~0u, (lane & 2) ? t0 : t1, 2);
        #pragma unroll
        for (int o = 4; o < 32; o <<= 1) t += __shfl_xor_sync(~0u, t, o);
        if (lane < 4) {
          const float gv = __fdividef(1.f, 1.f + exp_acc(-bf16_round(t)));
          const uint32_t w = (pack_bf2(gv, gv) & 0xffffu) | (tag << 16);
          asm volatile("st.relaxed.gpu.global.u32 [%0], %1;" :: "l"(&g_gate[cta * 16 + aw * 4 + lane]), "r"(w) : "memory");
        }
      }
      STAMP(2);
      asm volatile("barrier.cluster.wait.aligned;" ::: "memory");
      mbar_wait(mb + MB_URDY);
      if (at == 0) __stcg(&g_epoch[cta], epoch);
      #pragma unroll 1
      for (int kk = 0; kk < 2; kk++) {
        uint32_t x[4], y[4]; int it = 0; bool ok;
        do {
          ok = true;
          #pragma unroll
          for (int k = 0; k < 4; k++) {
            const uint32_t* gp = &g_gate[64 * (aw + 4 * k + 16 * kk) + lane];
            asm volatile("ld.relaxed.gpu.global.u32 %0, [%1];" : "=r"(x[k]) : "l"(gp) : "memory");
            asm volatile("ld.relaxed.gpu.global.u32 %0, [%1];" : "=r"(y[k]) : "l"(gp + 32) : "memory");
          }
          #pragma unroll
          for (int k = 0; k < 4; k++) ok = ok && (x[k] >> 16) == tag && (y[k] >> 16) == tag;
        } while (!ok && ++it < (1 << 18));
        #pragma unroll
        for (int k = 0; k < 4; k++) {
          uint32_t a = sb + SM_GW + ((aw + 4 * k + 16 * kk) * 40 + lane) * 4;
          sts32(a, __byte_perm(y[k], x[k], 0x5410));
          sts32(a + 5120, pack_bf2(1.f - bf_lo(y[k]), 1.f - bf_lo(x[k])));
          const uint32_t ge = sb + SM_GE + ((aw + 4 * k + 16 * kk) * 32 + (lane >> 4) * 8 + (lane & 7)) * 4 + ((lane >> 3) & 1) * 2;
          sts16(ge, x[k]); sts16(ge + 64, y[k]);
        }
      }
      warp_arrive(mb + MB_GW, lane);
      STAMP(4);
    }
    bar_sync(12, 256);
    #pragma unroll 1
    for (int c = 0; c < 4; c++) {
      const uint32_t yb = sb + (c < 2 ? SM_Y01 + c * Y_CH : SM_Y23 + (c - 2) * 8 * GSLOT);
      if (c == 0) mbar_wait(mb + MB_G23);
      if (at >= 200) {
        const int i = at - 200;
        sts128(yb + (i < 28 ? i * 16 : Y3_OFF - 512 + (i - 28) * 16), 0, 0, 0, 0);
      }
      if (at >= 6 && at < 200) ytab_chunk(sb + SM_UA + c * UA_CH + 63 * 16, yb, at - 8);
      warp_arrive(mb + MB_Y + 8 * c, lane);
      STAMP(5 + c);
    }
    {
      const int k = 7 - aw;
      const uint32_t tk = sb + SM_T + k * 4096 + lane * 16, t3 = sb + SM_T3 + k * 2048 + lane * 16;
      mbar_wait(mb + MB_LOC + 8 * k);
      STAMP(11);
      #pragma unroll
      for (int i = 0; i < 4; i++) {
        const int hf = (i >> 1) ^ rank ^ 1, o = (i & 1) * 512;
        const uint4 a = lds128(tk + hf * 2048 + o), b = lds128(tk + hf * 2048 + 1024 + o), c = k ? lds128(t3 + hf * 1024 + o) : make_uint4(0, 0, 0, 0);
        const uint32_t s0 = hadd(hadd(a.x, b.x), c.x), s1 = hadd(hadd(a.y, b.y), c.y), s2 = hadd(hadd(a.z, b.z), c.z), s3 = hadd(hadd(a.w, b.w), c.w);
        if (i < 2)
          asm volatile("st.async.weak.shared::cluster.mbarrier::complete_tx::bytes.v4.u32 [%0], {%1,%2,%3,%4}, [%5];"
                       :: "r"(mapa(sb + SM_RX + k * 1024 + lane * 16 + o, rank ^ 1)), "r"(s0), "r"(s1), "r"(s2), "r"(s3), "r"(mapa(mb + MB_RX + 8 * k, rank ^ 1)) : "memory");
        else sts128(t3 + hf * 1024 + o, s0, s1, s2, s3);
      }
      __syncwarp();
      mbar_wait(mb + MB_RX + 8 * k);
      STAMP(12);
      const int m = lane >> 3, j = lane & 7;
      const uint32_t src = (((j >> 2) == rank) ? sb + SM_T3 + k * 2048 + rank * 1024 : sb + SM_RX + k * 1024) + (j & 3) * 256;
      const uint32_t ob = sb + SM_T + k * 4096;
      #pragma unroll
      for (int it = 0; it < 4; it++) {
        const int c16 = 4 * it + m;
        uint32_t r[4];
        ldsm4t(src + ((c16 ^ (rank * 2 + (c16 >> 3)) ^ j) * 16), r);
        stsm4(ob + (it * 32 + lane) * 16, r);
      }
      fence_async();
      __syncwarp();
      if (lane == 0) {
        asm volatile("cp.async.bulk.tensor.2d.global.shared::cta.bulk_group [%0, {%2, %3}], [%1];"
                     :: "l"((uint64_t)&tmap_o), "r"(ob), "r"((cta >> 1) * 8), "r"(k * 256 + rank * 128) : "memory");
        asm volatile("cp.async.bulk.commit_group;" ::: "memory");
        asm volatile("cp.async.bulk.wait_group.read 0;" ::: "memory");
      }
      __syncwarp();
      STAMP(13);
    }
    asm volatile("barrier.cluster.arrive.relaxed.aligned;" ::: "memory");
    asm volatile("barrier.cluster.wait.aligned;" ::: "memory");
    STAMP(14);
    STAMP_DUMP();
  }
}

typedef CUresult (*EncodeFn)(CUtensorMap*, CUtensorMapDataType, cuuint32_t, void*, const cuuint64_t*, const cuuint64_t*,
                             const cuuint32_t*, const cuuint32_t*, CUtensorMapInterleave, CUtensorMapSwizzle,
                             CUtensorMapL2promotion, CUtensorMapFloatOOBfill);
}

extern "C" void kernel_launch(void* const* d_in, const int* in_sizes, int n_in, void* d_out, int out_size) {
  (void)in_sizes; (void)n_in; (void)out_size;
  static EncodeFn enc = nullptr;
  if (!enc) {
    void* fn = nullptr; cudaDriverEntryPointQueryResult qr;
    cudaGetDriverEntryPoint("cuTensorMapEncodeTiled", &fn, cudaEnableDefault, &qr);
    enc = (EncodeFn)fn;
    cudaFuncSetAttribute(ssm_gated_kernel, cudaFuncAttributeMaxDynamicSharedMemorySize, SM_TOTAL + STAMP_EXTRA);
  }
  CUtensorMap tm;
  cuuint64_t gd[2] = {(cuuint64_t)DIM, (cuuint64_t)SEQ}; cuuint64_t gs[1] = {(cuuint64_t)DIM * 2};
  cuuint32_t bd[2] = {8, 256}; cuuint32_t es[2] = {1, 1};
  enc(&tm, CU_TENSOR_MAP_DATA_TYPE_BFLOAT16, 2, d_in[0], gd, gs, bd, es, CU_TENSOR_MAP_INTERLEAVE_NONE,
      CU_TENSOR_MAP_SWIZZLE_NONE, CU_TENSOR_MAP_L2_PROMOTION_L2_128B, CU_TENSOR_MAP_FLOAT_OOB_FILL_NONE);
  CUtensorMap to;
  cuuint32_t bo[2] = {8, 128};
  enc(&to, CU_TENSOR_MAP_DATA_TYPE_BFLOAT16, 2, d_out, gd, gs, bo, es, CU_TENSOR_MAP_INTERLEAVE_NONE,
      CU_TENSOR_MAP_SWIZZLE_NONE, CU_TENSOR_MAP_L2_PROMOTION_NONE, CU_TENSOR_MAP_FLOAT_OOB_FILL_NONE);
  Params P;
  typedef const __nv_bfloat16* bp;
  P.u = (bp)d_in[0];
  const int mi[10] = {1, 2, 5, 6, 10, 11, 12, 13, 3, 4}, vi[4] = {7, 14, 8, 15};
  for (int i = 0; i < 10; i++) P.pm[i] = (bp)d_in[mi[i]];
  for (int i = 0; i < 4; i++) P.pv[i] = (bp)d_in[vi[i]];
  P.gate_w = (bp)d_in[16];
  P.out = (__nv_bfloat16*)d_out;
  ssm_gated_kernel<<<NCTA, NTHR, SM_TOTAL + STAMP_EXTRA, cudaStreamPerThread>>>(tm, to, P);
}
```

```cpp
#include <cuda_runtime.h>
#include <cuda_bf16.h>
#include <cuda_fp16.h>
#include <cuda.h>
#include <stdint.h>

#define STAMP(i) __syncwarp()
#define STAMP_EXTRA 0
#define STAMP_DUMP() do {} while (0)

namespace {

constexpr int SEQ = 2048, DIM = 512, NMODE = 128;
constexpr int NCTA = 128, NTHR = 768;

constexpr int GSLOT   = 3584;
constexpr int GBUF    = 16 * GSLOT;
constexpr int Y2_OFF = 128 * 4, Y3_OFF = (128 + 1536 + 128) * 4, Y_CH = (128 + 1536 + 128 + 1024) * 4;
constexpr int SM_G    = 0;
constexpr int SM_T    = 0;
constexpr int SM_T3   = SM_T + 32768;
constexpr int SM_Y23  = 16 * GSLOT + 1024;
constexpr int SM_RAW  = 2 * GBUF;
constexpr int SM_GW   = SM_RAW, SM_GE = SM_RAW + 10240;
constexpr int XS_CH   = 4 * 512 + 16;
constexpr int SM_XS   = SM_RAW + 16384;
constexpr int UA_ARR  = 74 * 16;
constexpr int UA_CH   = 4 * UA_ARR + 16;
constexpr int SM_RX   = SM_XS + 8320;
constexpr int SM_UA   = SM_RX + 8192;
constexpr int TW_W = 32, TW_X = 576, TW_2 = 656, TW_3 = 736, TW_TOT = 816;
constexpr int TAB_SZ  = TW_TOT * 4;
constexpr int SM_TAB  = SM_UA + 4 * UA_CH;
constexpr int SM_Y01  = SM_TAB + 8 * TAB_SZ;
constexpr int SM_ROW  = SM_Y01;
constexpr int SM_PRM  = SM_Y01 + 2 * Y_CH;
constexpr int SM_MX   = SM_PRM + 10240 + 64;
constexpr int SM_BAR  = SM_MX + 128;
constexpr int SM_TOTAL = SM_BAR + 256;
constexpr int MB_PRM = 0, MB_U = 8, MB_PEER = 16, MB_URDY = 24, MB_ROW = 32, MB_G1 = 40, MB_GW = 48, MB_G23 = 56, MB_Y = 64  , MB_LOC = 96, MB_RX = 160;
static_assert(SM_TOTAL + STAMP_EXTRA <= 232448, "smem");
static_assert(1024 + Y_CH <= 8 * GSLOT && SM_T3 + 16384 <= GBUF, "alias");
static_assert(SM_UA % 128 == 0 && SM_XS % 128 == 0 && SM_TAB % 16 == 0 && SM_Y01 % 16 == 0 && Y_CH % 16 == 0 && SM_T % 128 == 0, "align");

__device__ uint32_t g_gate[SEQ];
__device__ uint32_t g_epoch[NCTA];

struct Params {
  const __nv_bfloat16* u;
  const __nv_bfloat16* pm[10];
  const __nv_bfloat16* pv[4];
  const __nv_bfloat16* gate_w;
  __nv_bfloat16* out;
};

__device__ __forceinline__ void wgmma_n32(float* d, const uint32_t* a, uint64_t desc) {
  asm volatile("wgmma.mma_async.sync.aligned.m64n32k16.f32.bf16.bf16 {%0, %1, %2, %3, %4, %5, %6, %7, %8, %9, %10, %11, %12, %13, %14, %15}, {%16, %17, %18, %19}, %20, 1, 1, 1, 0;\n"
    : "+f"(d[0]), "+f"(d[1]), "+f"(d[2]), "+f"(d[3]), "+f"(d[4]), "+f"(d[5]), "+f"(d[6]), "+f"(d[7]), "+f"(d[8]), "+f"(d[9]), "+f"(d[10]), "+f"(d[11]), "+f"(d[12]), "+f"(d[13]), "+f"(d[14]), "+f"(d[15])
    : "r"(a[0]), "r"(a[1]), "r"(a[2]), "r"(a[3]), "l"(desc));
}

__device__ __forceinline__ void wgmma_n40(float* d, const uint32_t* a, uint64_t desc) {
  asm volatile("wgmma.mma_async.sync.aligned.m64n40k16.f32.bf16.bf16 {%0, %1, %2, %3, %4, %5, %6, %7, %8, %9, %10, %11, %12, %13, %14, %15, %16, %17, %18, %19}, {%20, %21, %22, %23}, %24, 1, 1, 1, 0;\n"
    : "+f"(d[0]), "+f"(d[1]), "+f"(d[2]), "+f"(d[3]), "+f"(d[4]), "+f"(d[5]), "+f"(d[6]), "+f"(d[7]), "+f"(d[8]), "+f"(d[9]), "+f"(d[10]), "+f"(d[11]), "+f"(d[12]), "+f"(d[13]), "+f"(d[14]), "+f"(d[15]), "+f"(d[16]), "+f"(d[17]), "+f"(d[18]), "+f"(d[19])
    : "r"(a[0]), "r"(a[1]), "r"(a[2]), "r"(a[3]), "l"(desc));
}

__device__ __forceinline__ void wgmma_n48(float* d, const uint32_t* a, uint64_t desc) {
  asm volatile("wgmma.mma_async.sync.aligned.m64n48k16.f32.bf16.bf16 {%0, %1, %2, %3, %4, %5, %6, %7, %8, %9, %10, %11, %12, %13, %14, %15, %16, %17, %18, %19, %20, %21, %22, %23}, {%24, %25, %26, %27}, %28, 1, 1, 1, 0;\n"
    : "+f"(d[0]), "+f"(d[1]), "+f"(d[2]), "+f"(d[3]), "+f"(d[4]), "+f"(d[5]), "+f"(d[6]), "+f"(d[7]), "+f"(d[8]), "+f"(d[9]), "+f"(d[10]), "+f"(d[11]), "+f"(d[12]), "+f"(d[13]), "+f"(d[14]), "+f"(d[15]), "+f"(d[16]), "+f"(d[17]), "+f"(d[18]), "+f"(d[19]), "+f"(d[20]), "+f"(d[21]), "+f"(d[22]), "+f"(d[23])
    : "r"(a[0]), "r"(a[1]), "r"(a[2]), "r"(a[3]), "l"(desc));
}

__device__ __forceinline__ void wgmma_n56(float* d, const uint32_t* a, uint64_t desc) {
  asm volatile("wgmma.mma_async.sync.aligned.m64n56k16.f32.bf16.bf16 {%0, %1, %2, %3, %4, %5, %6, %7, %8, %9, %10, %11, %12, %13, %14, %15, %16, %17, %18, %19, %20, %21, %22, %23, %24, %25, %26, %27}, {%28, %29, %30, %31}, %32, 1, 1, 1, 0;\n"
    : "+f"(d[0]), "+f"(d[1]), "+f"(d[2]), "+f"(d[3]), "+f"(d[4]), "+f"(d[5]), "+f"(d[6]), "+f"(d[7]), "+f"(d[8]), "+f"(d[9]), "+f"(d[10]), "+f"(d[11]), "+f"(d[12]), "+f"(d[13]), "+f"(d[14]), "+f"(d[15]), "+f"(d[16]), "+f"(d[17]), "+f"(d[18]), "+f"(d[19]), "+f"(d[20]), "+f"(d[21]), "+f"(d[22]), "+f"(d[23]), "+f"(d[24]), "+f"(d[25]), "+f"(d[26]), "+f"(d[27])
    : "r"(a[0]), "r"(a[1]), "r"(a[2]), "r"(a[3]), "l"(desc));
}

__device__ __forceinline__ void wgmma_n64(float* d, const uint32_t* a, uint64_t desc) {
  asm volatile("wgmma.mma_async.sync.aligned.m64n64k16.f32.bf16.bf16 {%0, %1, %2, %3, %4, %5, %6, %7, %8, %9, %10, %11, %12, %13, %14, %15, %16, %17, %18, %19, %20, %21, %22, %23, %24, %25, %26, %27, %28, %29, %30, %31}, {%32, %33, %34, %35}, %36, 1, 1, 1, 0;\n"
    : "+f"(d[0]), "+f"(d[1]), "+f"(d[2]), "+f"(d[3]), "+f"(d[4]), "+f"(d[5]), "+f"(d[6]), "+f"(d[7]), "+f"(d[8]), "+f"(d[9]), "+f"(d[10]), "+f"(d[11]), "+f"(d[12]), "+f"(d[13]), "+f"(d[14]), "+f"(d[15]), "+f"(d[16]), "+f"(d[17]), "+f"(d[18]), "+f"(d[19]), "+f"(d[20]), "+f"(d[21]), "+f"(d[22]), "+f"(d[23]), "+f"(d[24]), "+f"(d[25]), "+f"(d[26]), "+f"(d[27]), "+f"(d[28]), "+f"(d[29]), "+f"(d[30]), "+f"(d[31])
    : "r"(a[0]), "r"(a[1]), "r"(a[2]), "r"(a[3]), "l"(desc));
}

__device__ __forceinline__ uint32_t smem_u32(const void* p) { return (uint32_t)__cvta_generic_to_shared(p); }
__device__ __forceinline__ uint64_t mkdesc(uint32_t addr, uint32_t lbo, uint32_t sbo) {
  return (uint64_t)((addr & 0x3FFFF) >> 4) | ((uint64_t)(lbo >> 4) << 16) | ((uint64_t)(sbo >> 4) << 32);
}
__device__ __forceinline__ uint32_t lds32(uint32_t a) { uint32_t v; asm volatile("ld.shared.u32 %0, [%1];" : "=r"(v) : "r"(a) : "memory"); return v; }
__device__ __forceinline__ uint4 lds128(uint32_t a) { uint4 v; asm volatile("ld.shared.v4.u32 {%0,%1,%2,%3}, [%4];" : "=r"(v.x), "=r"(v.y), "=r"(v.z), "=r"(v.w) : "r"(a) : "memory"); return v; }
__device__ __forceinline__ float ldsbf(uint32_t a) { uint16_t v; asm volatile("ld.shared.u16 %0, [%1];" : "=h"(v) : "r"(a) : "memory"); return __uint_as_float((uint32_t)v << 16); }
__device__ __forceinline__ void sts16(uint32_t a, uint32_t v) { asm volatile("st.shared.u16 [%0], %1;" :: "r"(a), "h"((uint16_t)v) : "memory"); }
__device__ __forceinline__ void sts32(uint32_t a, uint32_t v) { asm volatile("st.shared.u32 [%0], %1;" :: "r"(a), "r"(v) : "memory"); }
__device__ __forceinline__ void sts128(uint32_t a, uint32_t x, uint32_t y, uint32_t z, uint32_t w) { asm volatile("st.shared.v4.u32 [%0], {%1,%2,%3,%4};" :: "r"(a), "r"(x), "r"(y), "r"(z), "r"(w) : "memory"); }
__device__ __forceinline__ void ldsm4t(uint32_t a, uint32_t* r) {
  asm volatile("ldmatrix.sync.aligned.m8n8.x4.trans.shared.b16 {%0,%1,%2,%3}, [%4];" : "=r"(r[0]), "=r"(r[1]), "=r"(r[2]), "=r"(r[3]) : "r"(a) : "memory");
}
__device__ __forceinline__ void mma_f16(float* c, const uint32_t* a, const uint32_t* b) {
  asm volatile("mma.sync.aligned.m16n8k16.row.col.f32.f16.f16.f32 {%0,%1,%2,%3}, {%4,%5,%6,%7}, {%8,%9}, {%0,%1,%2,%3};"
    : "+f"(c[0]), "+f"(c[1]), "+f"(c[2]), "+f"(c[3]) : "r"(a[0]), "r"(a[1]), "r"(a[2]), "r"(a[3]), "r"(b[0]), "r"(b[1]));
}
__device__ __forceinline__ void stsm4(uint32_t a, const uint32_t* r) {
  asm volatile("stmatrix.sync.aligned.m8n8.x4.shared.b16 [%0], {%1,%2,%3,%4};" :: "r"(a), "r"(r[0]), "r"(r[1]), "r"(r[2]), "r"(r[3]) : "memory");
}
__device__ __forceinline__ void stsm4t(uint32_t a, const uint32_t* r) {
  asm volatile("stmatrix.sync.aligned.m8n8.x4.trans.shared.b16 [%0], {%1,%2,%3,%4};" :: "r"(a), "r"(r[0]), "r"(r[1]), "r"(r[2]), "r"(r[3]) : "memory");
}
__device__ __forceinline__ void mma_bf16(float* c, uint32_t a0, uint32_t a1, uint32_t a2, uint32_t a3, const uint32_t* b) {
  asm volatile("mma.sync.aligned.m16n8k16.row.col.f32.bf16.bf16.f32 {%0,%1,%2,%3}, {%4,%5,%6,%7}, {%8,%9}, {%0,%1,%2,%3};"
    : "+f"(c[0]), "+f"(c[1]), "+f"(c[2]), "+f"(c[3]) : "r"(a0), "r"(a1), "r"(a2), "r"(a3), "r"(b[0]), "r"(b[1]));
}
__device__ __forceinline__ void bar_sync(int id, int n) { asm volatile("bar.sync %0, %1;" :: "r"(id), "r"(n) : "memory"); }
__device__ __forceinline__ void bar_arrive(int id, int n) { asm volatile("bar.arrive %0, %1;" :: "r"(id), "r"(n) : "memory"); }
__device__ __forceinline__ float ex2f(float x) { float y; asm("ex2.approx.ftz.f32 %0, %1;" : "=f"(y) : "f"(x)); return y; }
__device__ __forceinline__ float sinaf(float x) { float y; asm("sin.approx.ftz.f32 %0, %1;" : "=f"(y) : "f"(x)); return y; }
__device__ __forceinline__ float cosaf(float x) { float y; asm("cos.approx.ftz.f32 %0, %1;" : "=f"(y) : "f"(x)); return y; }
__device__ __forceinline__ uint32_t pack_h2(float lo, float hi) { uint32_t r; asm("cvt.rn.f16x2.f32 %0, %1, %2;" : "=r"(r) : "f"(hi), "f"(lo)); return r; }
__device__ __forceinline__ uint32_t pack_bf2(float lo, float hi) { uint32_t r; asm("cvt.rn.bf16x2.f32 %0, %1, %2;" : "=r"(r) : "f"(hi), "f"(lo)); return r; }
__device__ __forceinline__ float bf_lo(uint32_t v) { return __uint_as_float(v << 16); }
__device__ __forceinline__ float bf_hi(uint32_t v) { return __uint_as_float(v & 0xffff0000u); }
__device__ __forceinline__ float bf16_round(float x) { return __bfloat162float(__float2bfloat16_rn(x)); }
__device__ __forceinline__ uint32_t hadd(uint32_t a, uint32_t b) { __nv_bfloat162 r = __hadd2(*(__nv_bfloat162*)&a, *(__nv_bfloat162*)&b); return *(uint32_t*)&r; }
__device__ __forceinline__ float exp_acc(float x) {
  const float L = 1.4426950408889634f, Ll = 1.9259629911266175e-8f;
  float t = x * L, r = fmaf(x, L, -t); r = fmaf(x, Ll, r);
  return ex2f(t) * fmaf(r, 0.6931471805599453f, 1.f);
}
__device__ __forceinline__ void mbar_init(uint32_t a, int n) { asm volatile("mbarrier.init.shared.b64 [%0], %1;" :: "r"(a), "r"(n)); }
__device__ __forceinline__ void mbar_arrive(uint32_t a) { asm volatile("mbarrier.arrive.shared.b64 _, [%0];" :: "r"(a) : "memory"); }
__device__ __forceinline__ void mbar_expect(uint32_t a, int bytes) { asm volatile("mbarrier.arrive.expect_tx.shared.b64 _, [%0], %1;" :: "r"(a), "r"(bytes) : "memory"); }
__device__ __forceinline__ void mbar_wait(uint32_t a) {
  uint32_t ok = 0; int it = 0;
  while (!ok && it++ < (1 << 20))
    asm volatile("{ .reg .pred p; mbarrier.try_wait.parity.shared.b64 p, [%1], 0, 2000; selp.u32 %0, 1, 0, p; }" : "=r"(ok) : "r"(a) : "memory");
}
__device__ __forceinline__ void warp_arrive(uint32_t a, int lane) { __syncwarp(); if (lane == 0) mbar_arrive(a); }
__device__ __forceinline__ void fence_async() { asm volatile("fence.proxy.async.shared::cta;" ::: "memory"); }
__device__ __forceinline__ uint32_t mapa(uint32_t a, uint32_t rank) { uint32_t r; asm("mapa.shared::cluster.u32 %0, %1, %2;" : "=r"(r) : "r"(a), "r"(rank)); return r; }
__device__ __forceinline__ void dsmem_copy(uint32_t dst, uint32_t src, int bytes, uint32_t mb) {
  asm volatile("cp.async.bulk.shared::cluster.shared::cta.mbarrier::complete_tx::bytes [%0], [%1], %2, [%3];" :: "r"(dst), "r"(src), "r"(bytes), "r"(mb) : "memory");
}
__device__ __forceinline__ void bulk_g2s(uint32_t dst, const void* src, int bytes, uint32_t mb) {
  asm volatile("cp.async.bulk.shared::cluster.global.mbarrier::complete_tx::bytes [%0], [%1], %2, [%3];" :: "r"(dst), "l"(src), "r"(bytes), "r"(mb) : "memory");
}
__device__ __forceinline__ void wg_fence() { asm volatile("wgmma.fence.sync.aligned;" ::: "memory"); }
__device__ __forceinline__ void wg_commit() { asm volatile("wgmma.commit_group.sync.aligned;" ::: "memory"); }
template <int N> __device__ __forceinline__ void wg_wait() { asm volatile("wgmma.wait_group.sync.aligned %0;" :: "n"(N) : "memory"); }
template <int N> __device__ __forceinline__ void fence_acc(float* d) {
  #pragma unroll
  for (int i = 0; i < N; i++) asm volatile("" : "+f"(d[i]) :: "memory");
}

struct cf { float x, y; };
__device__ __forceinline__ cf cmul(cf a, cf b) { cf r; r.x = a.x * b.x - a.y * b.y; r.y = a.x * b.y + a.y * b.x; return r; }
__device__ __forceinline__ cf cmulc(cf a, cf b) { cf r; r.x = a.x * b.x + a.y * b.y; r.y = a.y * b.x - a.x * b.y; return r; }
__device__ __forceinline__ cf csq(cf a) { cf r; r.x = a.x * a.x - a.y * a.y; r.y = (a.x + a.x) * a.y; return r; }
__device__ __forceinline__ cf cexp_fast(float a2, float th, float x) {
  float e = ex2f(a2 * x), ph = th * x; cf r; r.x = e * cosaf(ph); r.y = e * sinaf(ph); return r;
}
struct hp { uint32_t r, i; };
__device__ __forceinline__ hp hbro(cf m) { hp h; h.r = pack_h2(m.x, m.x); h.i = pack_h2(m.y, m.y); return h; }
template <bool CONJ> __device__ __forceinline__ hp hmul(hp a, hp m) {
  const __half2 ar = *(__half2*)&a.r, ai = *(__half2*)&a.i, mr = *(__half2*)&m.r, mi = CONJ ? __hneg2(*(__half2*)&m.i) : *(__half2*)&m.i;
  const __half2 x = __hfma2(ar, mr, __hneg2(__hmul2(ai, mi))), y = __hfma2(ar, mi, __hmul2(ai, mr));
  hp o; o.r = *(uint32_t*)&x; o.i = *(uint32_t*)&y; return o;
}
__device__ __forceinline__ hp hlo(hp a, hp b) { hp o; o.r = __byte_perm(a.r, b.r, 0x5410); o.i = __byte_perm(a.i, b.i, 0x5410); return o; }
__device__ __forceinline__ void put4(uint32_t a, hp p0, hp p1, hp p2, hp p3) {
  sts128(a, p0.r, p1.r, p2.r, p3.r); sts128(a + 128, p0.i, p1.i, p2.i, p3.i);
}

struct Pow { hp t0, z, m2, m4, m256, m512, m1024, b0, m16, m32; uint32_t m64, m128; };
__device__ __forceinline__ void gen_powers(Pow& p, float al, float tt, cf c) {
  const cf w1 = cexp_fast(al, tt, 1.f), w64 = cexp_fast(al, tt, 64.f);
  const cf w2 = csq(w1), w4 = csq(w2), w8 = csq(w4), w16 = csq(w8), w32 = csq(w16);
  const cf w128 = csq(w64), w256 = csq(w128), w512 = csq(w256), w1024 = csq(w512);
  const cf c1 = cmulc(c, w1), c512 = cmulc(c, w512), c768 = cmulc(c512, w256);
  p.t0.r = pack_h2(c.x, c1.x); p.t0.i = pack_h2(c.y, c1.y);
  p.z.r = pack_h2(c512.x, c768.x); p.z.i = pack_h2(c512.y, c768.y);
  p.m2 = hbro(w2); p.m4 = hbro(w4); p.m256 = hbro(w256); p.m512 = hbro(w512); p.m1024 = hbro(w1024);
  p.b0.r = pack_h2(1.f, w8.x); p.b0.i = pack_h2(0.f, w8.y);
  p.m16 = hbro(w16); p.m32 = hbro(w32); p.m64 = pack_h2(w64.x, w64.y); p.m128 = pack_h2(w128.x, w128.y);
}
constexpr int KSLOT = 1024;
__device__ __forceinline__ void gen_store(const Pow& p, uint32_t gb, uint32_t gm) {
  const uint32_t bb = gb + 256;
  hp t1 = hmul<true>(p.t0, p.m2), t2 = hmul<true>(p.t0, p.m4), t3 = hmul<true>(t1, p.m4);
  put4(bb, p.t0, t1, t2, t3);
  const hp z4 = hmul<true>(p.z, p.m4);
  hp u0, u1; u0.r = __byte_perm(p.z.r, z4.r, 0x5410); u0.i = __byte_perm(p.z.i, z4.i, 0x5410);
  u1.r = __byte_perm(p.z.r, z4.r, 0x7632); u1.i = __byte_perm(p.z.i, z4.i, 0x7632);
  put4(bb + 256, hmul<true>(hlo(p.t0, t1), p.m256), hmul<true>(hlo(t2, t3), p.m256), u0, u1);
  u0 = hmul<true>(p.z, p.m512); u1 = hmul<true>(p.z, p.m1024);
  const hp u2 = hmul<true>(u0, p.m1024);
  put4(bb + 512, u0, u1, u2, u2);
  t1 = hmul<false>(p.b0, p.m16); t2 = hmul<false>(p.b0, p.m32); t3 = hmul<false>(t1, p.m32);
  put4(gb, p.b0, t1, t2, t3);
  sts16(gm, p.m64); sts16(gm + 4, p.m64 >> 16); sts16(gm + 128, p.m128); sts16(gm + 132, p.m128 >> 16);
  __syncwarp();
}
__device__ __forceinline__ void gen_contract(float* d, uint32_t la, uint32_t lb, uint32_t lm, uint32_t zr) {
  #pragma unroll
  for (int ks = 0; ks < 4; ks++) {
    uint32_t fa[4], fc[4], fb[8];
    ldsm4t(la + ks * KSLOT, fb + 4);
    hp m64, m128, x, y;
    asm volatile("ld.shared.v2.u32 {%0,%1}, [%2];" : "=r"(m64.r), "=r"(m64.i) : "r"(lm + ks * 32) : "memory");
    asm volatile("ld.shared.v2.u32 {%0,%1}, [%2];" : "=r"(m128.r), "=r"(m128.i) : "r"(lm + ks * 32 + 128) : "memory");
    ldsm4t(lb + ks * KSLOT, fb);
    x.r = fb[6]; x.i = fb[7]; y = hmul<false>(x, m64);
    fa[0] = x.r + zr; fa[2] = x.i + zr; fa[1] = y.r; fa[3] = y.i;
    x = hmul<false>(x, m128); y = hmul<false>(y, m128);
    fc[0] = x.r; fc[2] = x.i; fc[1] = y.r; fc[3] = y.i;
    #pragma unroll
    for (int nt = 0; nt < 3; nt++) { mma_f16(d + 4 * nt, fa, fb + 2 * nt); mma_f16(d + 12 + 4 * nt, fc, fb + 2 * nt); }
  }
  __syncwarp();
}

template <int S> __device__ __forceinline__ void near_step(float* d, uint64_t ud, const uint32_t* a) {
  constexpr int arr = (S & 1) ? 0 : 2;
  constexpr int slot = (S & 1) ? (S - 1) / 2 : S / 2;
  const uint64_t desc = ud + (uint64_t)((arr * UA_ARR + slot * 16) >> 4);
  if constexpr (S < 16) wgmma_n64(d, a, desc);
  else if constexpr (S < 32) wgmma_n56(d, a, desc);
  else if constexpr (S < 34) wgmma_n48(d, a, desc);
  else if constexpr (S == 63) wgmma_n40(d, a, desc);
  else wgmma_n32(d, a, desc);
}
template <int S0, int NS> __device__ __forceinline__ void near_load(uint32_t (*a)[4], uint32_t wa, uint32_t zr) {
  a[0][2] = lds32(wa + (uint32_t)((2 * S0 - 1) * 32));
  #pragma unroll
  for (int i = 0; i < NS; i++) {
    a[i][0] = lds32(wa + (2 * (S0 + i)) * 32);
    a[i][1] = lds32(wa + (2 * (S0 + i) + 1) * 32);
  }
  #pragma unroll
  for (int i = 0; i < NS; i++) {
    a[i][3] = a[i][0] + zr;
    if (i + 1 < NS) a[i + 1][2] = a[i][1] + zr;
  }
}
template <int S0, int NS> __device__ __forceinline__ void near_issue(float* d, uint64_t ua, uint32_t (*a)[4]) {
  wg_fence();
  near_step<S0>(d, ua, a[0]);
  if constexpr (NS > 1) near_step<S0 + 1>(d, ua, a[1]);
  if constexpr (NS > 2) near_step<S0 + 2>(d, ua, a[2]);
  if constexpr (NS > 3) near_step<S0 + 3>(d, ua, a[3]);
  if constexpr (NS > 4) near_step<S0 + 4>(d, ua, a[4]);
  if constexpr (NS > 5) near_step<S0 + 5>(d, ua, a[5]);
  wg_commit();
}

__device__ __forceinline__ void sts2x(uint32_t o, const uint32_t* w) {
  const bool sw = (threadIdx.x >> 2) & 1;
  sts128(o + (sw ? 16 : 0), sw ? w[4] : w[0], sw ? w[5] : w[1], sw ? w[6] : w[2], sw ? w[7] : w[3]);
  sts128(o + (sw ? 0 : 16), sw ? w[0] : w[4], sw ? w[1] : w[5], sw ? w[2] : w[6], sw ? w[3] : w[7]);
}
__device__ __forceinline__ void ytab_chunk(uint32_t ub, uint32_t yb, int chi) {
  auto ca = [&](int c) { return ub + (c & 3) * UA_ARR - (c >> 2) * 16; };
  const uint4 z = lds128(ca(chi - 2)), a = lds128(ca(chi - 1)), b = lds128(ca(chi)), c = lds128(ca(chi + 1));
  const float v[23] = {bf_hi(z.z), bf_lo(z.w), bf_hi(z.w),
                       bf_lo(a.x), bf_hi(a.x), bf_lo(a.y), bf_hi(a.y), bf_lo(a.z), bf_hi(a.z), bf_lo(a.w), bf_hi(a.w),
                       bf_lo(b.x), bf_hi(b.x), bf_lo(b.y), bf_hi(b.y), bf_lo(b.z), bf_hi(b.z), bf_lo(b.w), bf_hi(b.w),
                       bf_lo(c.x), bf_hi(c.x), bf_lo(c.y), bf_hi(c.y)};
  float s[24];
  s[13] = 0.f; s[14] = v[13]; s[12] = -v[12];
  #pragma unroll
  for (int i = 15; i < 24; i++) s[i] = s[i - 1] + v[i - 1];
  #pragma unroll
  for (int i = 11; i >= 0; i--) s[i] = s[i + 1] - v[i];
  uint32_t w[8];
  {
    #pragma unroll
    for (int i = 0; i < 8; i++) w[i] = pack_bf2(s[i + 14] - s[i + 9], s[i + 9] - s[i + 6]);
    const int cp = (chi ^ ((chi >> 2) & 1)) * 32;
    uint32_t o = yb + Y2_OFF + cp;
    sts2x(o, w);
    if (chi < 128) {
      #pragma unroll
      for (int i = 0; i < 8; i++) w[i] = pack_bf2(s[i + 16] - s[i + 7], s[i + 7] - s[i]);
      o = yb + Y3_OFF + cp;
      sts2x(o, w);
    }
  }
}

__device__ __forceinline__ uint32_t ldv32(uint32_t a) { uint32_t v; asm volatile("ld.volatile.shared.u32 %0, [%1];" : "=r"(v) : "r"(a) : "memory"); return v; }
__device__ __forceinline__ void ld_frag(uint32_t* n, uint32_t x, int dp, int dm) { n[0] = ldv32(x); n[1] = ldv32(x + dp); n[2] = ldv32(x + dm); }
__device__ __forceinline__ void far_octet(float (*acc)[4], int j0, uint32_t yb, uint32_t kb, int g, int q, const uint32_t (*b2)[2]) {
  const int mu = g >> 1;
  const uint32_t zr = ldv32(kb);
  uint32_t a[4][4];
  const int dp = q < 2 ? -32 : 32;
  if (j0 >= 4) {
    const uint32_t ya = yb + Y2_OFF + (64 * (j0 - 8) + 48 - 16 * q + (q < 2 ? 8 : 0) + g) * 4;
    const int dm = (q == 0) ? -96 : (q == 2) ? -32 : -64;
    #pragma unroll
    for (int i = 0; i < 3; i++) ld_frag(a[i], ya + (3 - i) * 256, dp, dm);
    #pragma unroll
    for (int i = 0; i < 12; i++) {
      const int br = 3 - i;
      if ((i & 3) == 1 && j0 + br < 7) break;
      if (i + 3 < 12) ld_frag(a[(i + 3) & 3], ya + (br - 3) * 256, dp, dm);
      uint32_t* c = a[i & 3];
      c[3] = c[0] + zr;
      #pragma unroll
      for (int j = 0; j < 4; j++) { const int s = j - br; if (s >= 0 && s < 9) mma_bf16(acc[j], c[0], c[1], c[2], c[3], b2[s]); }
    }
  }
  if (j0 >= 12) {
    const uint32_t ya = yb + Y3_OFF + (64 * (j0 - 16) + 48 - 16 * q + (q < 2 ? 8 : 0) + g) * 4;
    #pragma unroll
    for (int i = 0; i < 3; i++) { a[i][0] = ldv32(ya + (3 - i) * 256); a[i][1] = ldv32(ya + (3 - i) * 256 + dp); }
    uint32_t b3[9][2];
    #pragma unroll
    for (int s = 0; s < 9; s++) { b3[s][0] = ldv32(kb + (TW_3 + mu + q + 8 * s) * 4); b3[s][1] = ldv32(kb + (TW_3 + mu + q + 8 * s + 4) * 4); }
    #pragma unroll
    for (int i = 0; i < 17; i++) {
      const int br = 3 - i;
      if ((i & 3) == 1 && j0 + br < 15) break;
      if (i + 3 < 18) { uint32_t* n = a[(i + 3) & 3]; n[0] = ldv32(ya + (br - 3) * 256); n[1] = ldv32(ya + (br - 3) * 256 + dp); }
      uint32_t* c = a[i & 3];
      c[2] = a[(i + 1) & 3][0] + zr; c[3] = a[(i + 1) & 3][1] + zr;
      #pragma unroll
      for (int j = 0; j < 4; j++) { const int s2 = j - br; if (s2 >= 0 && !(s2 & 1)) mma_bf16(acc[j], c[0], c[1], c[2], c[3], b3[s2 >> 1]); }
    }
  }
}

__global__ void __cluster_dims__(2, 1, 1) __launch_bounds__(NTHR, 1)
ssm_gated_kernel(const __grid_constant__ CUtensorMap tmap_u, const __grid_constant__ CUtensorMap tmap_o, const __grid_constant__ Params P) {
  extern __shared__ __align__(1024) unsigned char smem[];
  const uint32_t sb = smem_u32(smem);
  const int tid = threadIdx.x, warp = __shfl_sync(~0u, tid >> 5, 0), lane = tid & 31;
  const int g = lane >> 2, q = lane & 3;
  const int cta = blockIdx.x, c0 = cta * 4, rank = cta & 1;
  const uint32_t mb = sb + SM_BAR;
  if (tid == 0) {
    mbar_init(mb + MB_PRM, 1); mbar_init(mb + MB_ROW, 1);
    fence_async();
    mbar_expect(mb + MB_PRM, 10240 + 64);
    #pragma unroll
    for (int i = 0; i < 10; i++) bulk_g2s(sb + SM_PRM + i * 1024, P.pm[i] + c0 * NMODE, 1024, mb + MB_PRM);
    #pragma unroll
    for (int i = 0; i < 4; i++) bulk_g2s(sb + SM_PRM + 10240 + i * 16, P.pv[i] + (cta >> 1) * 8, 16, mb + MB_PRM);
  }
  if (tid == 32) {
    mbar_init(mb + MB_U, 1); mbar_init(mb + MB_URDY, 1);
    mbar_init(mb + MB_G1, 8); mbar_init(mb + MB_G23, 8); mbar_init(mb + MB_PEER, 1); mbar_init(mb + MB_GW, 4);
    #pragma unroll
    for (int i = 0; i < 4; i++) mbar_init(mb + MB_Y + 8 * i, 8);
    #pragma unroll
    for (int i = 0; i < 8; i++) { mbar_init(mb + MB_LOC + 8 * i, i ? 20 : 16); mbar_init(mb + MB_RX + 8 * i, 1); }
    asm volatile("fence.mbarrier_init.release.cluster;" ::: "memory");
    fence_async();
  }
  STAMP(0);

  if (warp < 16) {
    const int ch = warp >> 2, br = (warp >> 1) & 1, w0 = warp & 1;
    asm volatile("setmaxnreg.inc.sync.aligned.u32 96;");
    for (int i = tid; i < (SM_Y01 - SM_TAB) / 16; i += 512) sts128(sb + SM_TAB + i * 16, 0, 0, 0, 0);
    if (tid < 160) sts128(sb + SM_UA + (tid / 40) * UA_CH + ((tid / 10) & 3) * UA_ARR + (64 + tid % 10) * 16, 0, 0, 0, 0);
    fence_async();
    asm volatile("barrier.cluster.arrive.relaxed.aligned;" ::: "memory");
    bar_sync(0, NTHR);
    const uint32_t tab = sb + SM_TAB + (ch * 2 + br) * TAB_SZ;
    const uint32_t zr = lds32(tab);
    const uint32_t yb = sb + (ch < 2 ? SM_Y01 + ch * Y_CH : SM_Y23 + (ch - 2) * 8 * GSLOT);
    {
      const uint32_t gw = sb + SM_G + warp * (2 * GSLOT);
      const uint32_t gb = gw + (lane >> 3) * KSLOT + (lane & 7) * 16;
      const uint32_t gm = gw + 4 * KSLOT + (lane >> 1) * 8 + (lane & 1) * 2;
      const uint32_t la = gw + (((lane >> 3) * 128 + 768) & 1023) + (lane & 7) * 16;
      const uint32_t lb = gw + 256 + (lane >> 3) * 128 + (lane & 7) * 16;
      const uint32_t lm = gw + 4 * KSLOT + q * 8;
      float a2[2], th[2]; cf cc[2];
      const uint32_t pp = sb + SM_PRM + br * 4096 + ch * 256 + (w0 * 32 + lane) * 2;
      const uint32_t pl = sb + SM_PRM + 10240 + br * 16 + rank * 8 + ch * 2;
      mbar_wait(mb + MB_PRM);
      STAMP(1);
      const float dt = bf16_round(exp_acc(ldsbf(pl)));
      float mxf = 0.f;
      #pragma unroll
      for (int r = 0; r < 2; r++) {
        float are = ldsbf(pp + r * 128);
        if (br) are = -bf16_round(exp_acc(are));
        a2[r] = (are * dt) * 1.4426950408889634f; th[r] = ldsbf(pp + r * 128 + 1024) * dt;
        cf c = {ldsbf(pp + r * 128 + 2048), ldsbf(pp + r * 128 + 3072)}, dB = {dt + dt, 0.f};
        if (!br) { dB.x = dt * ldsbf(pp + r * 128 + 8192); dB.y = dt * ldsbf(pp + r * 128 + 9216); }
        c = cmul(c, dB); cc[r].x = c.x; cc[r].y = -c.y;
        mxf = fmaxf(mxf, fmaxf(fabsf(c.x), fabsf(c.y)));
      }
      const int e = min(max((int)(__reduce_max_sync(~0u, __float_as_uint(mxf)) >> 23), 1), 252);
      const float sc = __uint_as_float((uint32_t)(253 - e) << 23);
      float d[24];
      #pragma unroll
      for (int i = 0; i < 24; i++) d[i] = 0.f;
      {
        Pow p;
        cf c = cc[0]; c.x *= sc; c.y *= sc;
        gen_powers(p, a2[0], th[0], c);
        if (ch >= 2) bar_sync(5, 512);
        gen_store(p, gb, gm);
        if (ch < 2) bar_arrive(5, 512);
        STAMP(2);
        c = cc[1]; c.x *= sc; c.y *= sc;
        gen_powers(p, a2[1], th[1], c);
        gen_contract(d, la, lb, lm, zr);
        gen_store(p, gb, gm);
        STAMP(3);
        gen_contract(d, la, lb, lm, zr);
      }
      const float isc = __uint_as_float((uint32_t)(e + 1) << 23);
      const int jr = w0 * 16 + g;
      const uint32_t a0 = tab + (TW_W + 8 * jr + 2 * q) * 4;
      const uint32_t a1 = tab + (q < 2 ? TW_W + 256 + 8 * jr + 4 * q : TW_2 + 6 + 32 * (q - 2) + jr) * 4;
      const uint32_t a3 = tab + TW_3 * 4 + (6 + 64 * q + jr) * 2;
      float k[12];
      {
        #pragma unroll
        for (int i = 0; i < 3; i++) {
          sts128(gw + i * 512 + lane * 16, __float_as_uint((w0 ? d[4 * i] : d[12 + 4 * i]) * isc), __float_as_uint((w0 ? d[4 * i + 1] : d[13 + 4 * i]) * isc),
                 __float_as_uint((w0 ? d[4 * i + 2] : d[14 + 4 * i]) * isc), __float_as_uint((w0 ? d[4 * i + 3] : d[15 + 4 * i]) * isc));
        }
        const float own = (lane == 0 ? d[8] : d[4]) * isc;
        if (!w0 && (lane == 0 || lane == 2)) sts32(gw + 1536 + lane * 2, __float_as_uint(own));
        const float fo = __shfl_sync(~0u, own, q == 3 ? 0 : 2);
        bar_sync(1 + ch, 128);
        const uint32_t po = sb + SM_G + (warp ^ 1) * (2 * GSLOT) + lane * 16;
        #pragma unroll
        for (int i = 0; i < 3; i++) {
          const uint4 v = lds128(po + i * 512);
          k[4 * i]     = fmaf(w0 ? d[12 + 4 * i] : d[4 * i], isc, __uint_as_float(v.x));
          k[4 * i + 1] = fmaf(w0 ? d[13 + 4 * i] : d[4 * i + 1], isc, __uint_as_float(v.y));
          k[4 * i + 2] = fmaf(w0 ? d[14 + 4 * i] : d[4 * i + 2], isc, __uint_as_float(v.z));
          k[4 * i + 3] = fmaf(w0 ? d[15 + 4 * i] : d[4 * i + 3], isc, __uint_as_float(v.w));
        }
        if (w0 && g == 7 && (q & 1)) k[7] -= fo + __uint_as_float(lds32(po - lane * 16 + 1536 + (q == 3 ? 0 : 4)));
        warp_arrive(mb + (ch < 2 ? MB_G1 : MB_G23), lane);
      }
      if (jr == 0 && q == 0) k[0] += ldsbf(pl + 32);
      #pragma unroll
      for (int h = 0; h < 2; h++) {
        uint32_t w = pack_bf2(k[2 * h + 1], k[2 * h]);
        sts16(a0 + h * 256, w >> 16); sts32(a0 + h * 256 + 4, w); sts16(a0 + h * 256 + 10, w);
        w = pack_bf2(k[4 + 2 * h], k[5 + 2 * h]);
        if (q < 2) {
          const uint32_t a = a1 + h * 256, w0w = __byte_perm(w, w, 0x1010);
          if (h == 0 && jr == 0 && q == 0) sts16(a, w0w); else { sts16(a - 4, w0w); sts32(a, w0w); }
          sts32(a + 4, w0w); sts32(a + 8, __byte_perm(w, w, 0x1032)); sts16(a + 14, w >> 16);
        } else sts32(a1 + h * 32, w);
        w = pack_bf2(k[8 + 2 * h], k[9 + 2 * h]);
        if (q < 2 || (q == 2 && h == 0 && jr == 0)) sts16(a3 + h * 16, w);
        if (q < 2) sts16(a3 + h * 16 + 64, w >> 16);
        if (h == 0 && jr == 0 && q == 0) { sts16(tab + (TW_X + 1019 - 976) * 4, w); sts16(tab + (TW_X + 1020 - 976) * 4 + 2, w); }
      }
      bar_sync(1 + ch, 128);
      STAMP(4);
    }
    {
      const uint64_t ua = mkdesc(sb + SM_UA + ch * UA_CH, UA_ARR, 128);
      const uint32_t wa = tab + (TW_W + 16 * w0 + g - 2 * q - 16) * 4;
      float d[32];
      #pragma unroll
      for (int i = 0; i < 32; i++) d[i] = 0.f;
      uint32_t A[4][4], B[4][4];
      near_load<0, 4>(A, wa, zr);
      near_load<4, 4>(B, wa, zr);
      STAMP(6);
      mbar_wait(mb + MB_URDY);
      STAMP(7);
      fence_acc<32>(d);
      near_issue<0, 4>(d, ua, A);
      near_issue<4, 4>(d, ua, B);   wg_wait<1>();
      near_load<8, 4>(A, wa, zr);   near_issue<8, 4>(d, ua, A);   wg_wait<1>();
      near_load<12, 4>(B, wa, zr);  near_issue<12, 4>(d, ua, B);  wg_wait<1>();
      near_load<16, 4>(A, wa, zr);
      wg_wait<0>();
      fence_acc<32>(d);
      mbar_wait(mb + MB_GW);
      mbar_wait(mb + MB_G1);
      const int m = lane >> 3, tl = 7 - (lane & 7);
      const uint32_t ga = sb + SM_GW + br * 5120 + ((3 - q) * 40 + 16 * w0 + g) * 4;
      const int c16 = 4 * (tl & 3) + 2 * w0 + (m & 1);
      const uint32_t ta = sb + SM_T + (m >> 1) * 4096 + (tl >> 2) * 2048 + (br * 4 + ch) * 256 + ((c16 ^ (tl >> 1) ^ (rank * 4 + ch)) * 16);
      {
        uint32_t r[2];
        #pragma unroll
        for (int h = 0; h < 2; h++) {
          const uint32_t gw = lds32(ga + 8 * h * 4), y = pack_bf2(d[28 + 2 * h], d[29 + 2 * h]);
          const __nv_bfloat162 t2 = __hmul2(*(const __nv_bfloat162*)&y, *(const __nv_bfloat162*)&gw);
          r[h] = *(const uint32_t*)&t2;
        }
        asm volatile("stmatrix.sync.aligned.m8n8.x2.trans.shared.b16 [%0], {%1,%2};" :: "r"(ta), "r"(r[0]), "r"(r[1]) : "memory");
        warp_arrive(mb + MB_LOC, lane);
      }
      fence_acc<28>(d);
      near_issue<16, 4>(d, ua, A);
      near_load<20, 4>(B, wa, zr);  near_issue<20, 4>(d, ua, B);  wg_wait<1>();
      near_load<24, 4>(A, wa, zr);  near_issue<24, 4>(d, ua, A);  wg_wait<1>();
      near_load<28, 4>(B, wa, zr);  near_issue<28, 4>(d, ua, B);  wg_wait<1>();
      near_load<32, 2>(A, wa, zr);  near_issue<32, 2>(d, ua, A);  wg_wait<1>();
      near_load<63, 3>(B, wa - (uint32_t)((976 + TW_W - TW_X) * 4), zr);
      near_issue<63, 1>(d, ua, B);
      near_issue<64, 2>(d, ua, B + 1);
      wg_wait<0>();
      fence_acc<28>(d);
      STAMP(8);
      #pragma unroll
      for (int i = 1; i < 8; i += 2) {
        uint32_t r[4];
        #pragma unroll
        for (int kk = 0; kk < (i < 7 ? 4 : 2); kk++) {
          const int ii = i + (kk >> 1), h = kk & 1;
          const uint32_t gw = lds32(ga + (ii * 160 + 8 * h) * 4);
          const uint32_t y = pack_bf2(d[4 * (7 - ii) + 2 * h], d[4 * (7 - ii) + 2 * h + 1]);
          const __nv_bfloat162 t2 = __hmul2(*(const __nv_bfloat162*)&y, *(const __nv_bfloat162*)&gw);
          r[kk] = *(const uint32_t*)&t2;
        }
        if (i < 7) stsm4t(ta + i * 4096, r);
        else asm volatile("stmatrix.sync.aligned.m8n8.x2.trans.shared.b16 [%0], {%1,%2};" :: "r"(ta + i * 4096 - (m >> 1) * 4096), "r"(r[0]), "r"(r[1]) : "memory");
        __syncwarp();
        if (lane < (i < 7 ? 2 : 1)) mbar_arrive(mb + MB_LOC + 8 * (i + lane));
      }
    }
    STAMP(9);
    {
      const uint32_t kb = sb + SM_TAB + (ch * 2 + (g & 1)) * TAB_SZ;
      uint32_t b2[9][2];
      #pragma unroll
      for (int s = 0; s < 9; s++)
        asm volatile("ld.shared.v2.u32 {%0,%1}, [%2];" : "=r"(b2[s][0]), "=r"(b2[s][1]) : "r"(kb + (TW_2 + 2 * (g >> 1) + 2 * q + 8 * s) * 4) : "memory");
      mbar_wait(mb + MB_Y + 8 * ch);
      STAMP(10);
      const int c32 = lane, c16 = c32 & 15;
      const uint32_t t3a = sb + SM_T3 + (c32 >> 4) * 1024 + ch * 256 + ((c16 ^ (c32 >> 3) ^ (rank * 4 + ch)) * 16);
      #pragma unroll 1
      for (int ps = 0; ps < 2; ps++) {
        const int o4 = (warp + ch) & 3, oc = ps ? o4 + 4 : o4, j0 = 4 * oc;
        if (oc == 0) continue;
        float acc[4][4];
        uint32_t gq[4];
        #pragma unroll
        for (int j = 0; j < 4; j++) {
          gq[j] = lds32(sb + SM_GE + (32 * (j0 + j) + 8 * q + g) * 4);
          acc[j][0] = acc[j][1] = acc[j][2] = acc[j][3] = 0.f;
        }
        far_octet(acc, j0, yb, kb, g, q, b2);
        uint32_t r[4];
        #pragma unroll
        for (int j = 0; j < 4; j++)
          r[j] = pack_bf2(fmaf(bf_lo(gq[j]), acc[j][0] - acc[j][1], acc[j][1]), fmaf(bf_hi(gq[j]), acc[j][2] - acc[j][3], acc[j][3]));
        stsm4t(t3a + oc * 2048, r);
        warp_arrive(mb + MB_LOC + 8 * oc, lane);
        STAMP(11 + ps);
      }
    }
  } else {
    asm volatile("setmaxnreg.dec.sync.aligned.u32 48;");
    const int aw = warp - 16, at = tid - 512;
    const uint32_t epoch = __ldcg(&g_epoch[cta]) + 1u, tag = epoch & 0xffffu;
    asm volatile("barrier.cluster.arrive.relaxed.aligned;" ::: "memory");
    bar_sync(0, NTHR);
    STAMP(1);
    if (aw >= 4) {
      const int bw = aw - 4, bt = at - 128;
      if (bt == 0) {
        mbar_expect(mb + MB_ROW, 16384 + 1024);
        bulk_g2s(sb + SM_ROW, P.u + (size_t)cta * 16 * DIM, 16384, mb + MB_ROW);
        bulk_g2s(sb + SM_ROW + 16384, P.gate_w, 1024, mb + MB_ROW);
        mbar_expect(mb + MB_U, 16384);
        #pragma unroll
        for (int i = 0; i < 4; i++)
          asm volatile("cp.async.bulk.tensor.2d.shared::cluster.global.mbarrier::complete_tx::bytes [%0], [%1, {%3, %4}], [%2];"
                       :: "r"(sb + SM_RAW + i * 4096), "l"((uint64_t)&tmap_u), "r"(mb + MB_U), "r"((cta >> 1) * 8), "r"(rank * 1024 + i * 256) : "memory");
        mbar_expect(mb + MB_PEER, 8192);
        #pragma unroll
        for (int i = 0; i < 8; i++) mbar_expect(mb + MB_RX + 8 * i, 1024);
      }
      mbar_wait(mb + MB_U);
      STAMP(2);
      const int chs = (lane & 7) - rank * 4, m = lane >> 3;
      const uint32_t base = ((unsigned)chs < 4u) ? sb + SM_UA + chs * UA_CH + m * UA_ARR + (63 - rank * 32) * 16
                                                 : sb + SM_XS + 64 + (chs & 3) * XS_CH + m * 512 + 31 * 16;
      #pragma unroll
      for (int hh = 0; hh < 2; hh++) {
        uint32_t r[4][4];
        #pragma unroll
        for (int it = 0; it < 4; it++) ldsm4t(sb + SM_RAW + ((bw * 8 + hh * 4 + it) * 32 + lane) * 16, r[it]);
        #pragma unroll
        for (int it = 0; it < 4; it++) stsm4(base - (bw * 8 + hh * 4 + it) * 16, r[it]);
      }
      fence_async();
      asm volatile("barrier.cluster.wait.aligned;" ::: "memory");
      bar_sync(11, 128);
      if (lane < 4) {
        dsmem_copy(mapa(sb + SM_UA + bw * UA_CH + lane * UA_ARR + (32 - rank * 32) * 16, rank ^ 1),
                   sb + SM_XS + 64 + bw * XS_CH + lane * 512, 512, mapa(mb + MB_PEER, rank ^ 1));
      }
      STAMP(3);
      mbar_wait(mb + MB_PEER);
      if (bt == 0) mbar_arrive(mb + MB_URDY);
      STAMP(4);
    } else {
      mbar_wait(mb + MB_ROW);
      {
        const uint4 gw0 = lds128(sb + SM_ROW + 16384 + lane * 16), gw1 = lds128(sb + SM_ROW + 16384 + 512 + lane * 16);
        float s[4];
        #pragma unroll
        for (int r = 0; r < 4; r++) {
          const uint4 x0 = lds128(sb + SM_ROW + (aw * 4 + r) * 1024 + lane * 16), x1 = lds128(sb + SM_ROW + (aw * 4 + r) * 1024 + 512 + lane * 16);
          const uint32_t xv[8] = {x0.x, x0.y, x0.z, x0.w, x1.x, x1.y, x1.z, x1.w}, wv[8] = {gw0.x, gw0.y, gw0.z, gw0.w, gw1.x, gw1.y, gw1.z, gw1.w};
          float a = 0.f, b = 0.f;
          #pragma unroll
          for (int i = 0; i < 8; i++) {
            __nv_bfloat162 pr2 = __hmul2(*(const __nv_bfloat162*)&xv[i], *(const __nv_bfloat162*)&wv[i]);
            const uint32_t pv = *(uint32_t*)&pr2;
            a += bf_lo(pv); b += bf_hi(pv);
          }
          s[r] = a + b;
        }
        float t0 = (lane & 1) ? s[1] : s[0], t1 = (lane & 1) ? s[3] : s[2];
        t0 += __shfl_xor_sync(~0u, (lane & 1) ? s[0] : s[1], 1); t1 += __shfl_xor_sync(~0u, (lane & 1) ? s[2] : s[3], 1);
        float t = (lane & 2) ? t1 : t0;
        t += __shfl_xor_sync(~0u, (lane & 2) ? t0 : t1, 2);
        #pragma unroll
        for (int o = 4; o < 32; o <<= 1) t += __shfl_xor_sync(~0u, t, o);
        if (lane < 4) {
          const float gv = __fdividef(1.f, 1.f + exp_acc(-bf16_round(t)));
          const uint32_t w = (pack_bf2(gv, gv) & 0xffffu) | (tag << 16);
          asm volatile("st.relaxed.gpu.global.u32 [%0], %1;" :: "l"(&g_gate[cta * 16 + aw * 4 + lane]), "r"(w) : "memory");
        }
      }
      STAMP(2);
      asm volatile("barrier.cluster.wait.aligned;" ::: "memory");
      mbar_wait(mb + MB_URDY);
      #pragma unroll 1
      for (int kk = 0; kk < 2; kk++) {
        uint32_t x[4], y[4]; int it = 0; bool ok;
        do {
          ok = true;
          #pragma unroll
          for (int k = 0; k < 4; k++) {
            const uint32_t* gp = &g_gate[64 * (aw + 4 * k + 16 * kk) + lane];
            asm volatile("ld.relaxed.gpu.global.u32 %0, [%1];" : "=r"(x[k]) : "l"(gp) : "memory");
            asm volatile("ld.relaxed.gpu.global.u32 %0, [%1];" : "=r"(y[k]) : "l"(gp + 32) : "memory");
          }
          #pragma unroll
          for (int k = 0; k < 4; k++) ok = ok && (x[k] >> 16) == tag && (y[k] >> 16) == tag;
        } while (!ok && ++it < (1 << 18));
        #pragma unroll
        for (int k = 0; k < 4; k++) {
          uint32_t a = sb + SM_GW + ((aw + 4 * k + 16 * kk) * 40 + lane) * 4;
          sts32(a, __byte_perm(y[k], x[k], 0x5410));
          sts32(a + 5120, pack_bf2(1.f - bf_lo(y[k]), 1.f - bf_lo(x[k])));
          const uint32_t ge = sb + SM_GE + ((aw + 4 * k + 16 * kk) * 32 + (lane >> 4) * 8 + (lane & 7)) * 4 + ((lane >> 3) & 1) * 2;
          sts16(ge, x[k]); sts16(ge + 64, y[k]);
        }
      }
      warp_arrive(mb + MB_GW, lane);
      STAMP(4);
    }
    bar_sync(12, 256);
    if (at == 0) __stcg(&g_epoch[cta], epoch);
    #pragma unroll 1
    for (int c = 0; c < 4; c++) {
      const uint32_t yb = sb + (c < 2 ? SM_Y01 + c * Y_CH : SM_Y23 + (c - 2) * 8 * GSLOT);
      if (c == 0) mbar_wait(mb + MB_G23);
      if (at >= 200) {
        const int i = at - 200;
        sts128(yb + (i < 28 ? i * 16 : Y3_OFF - 512 + (i - 28) * 16), 0, 0, 0, 0);
      }
      if (at >= 6 && at < 200) ytab_chunk(sb + SM_UA + c * UA_CH + 63 * 16, yb, at - 8);
      warp_arrive(mb + MB_Y + 8 * c, lane);
      STAMP(5 + c);
    }
    {
      const int k = 7 - aw;
      const uint32_t tk = sb + SM_T + k * 4096 + lane * 16, t3 = sb + SM_T3 + k * 2048 + lane * 16;
      mbar_wait(mb + MB_LOC + 8 * k);
      STAMP(11);
      #pragma unroll
      for (int i = 0; i < 4; i++) {
        const int hf = (i >> 1) ^ rank ^ 1, o = (i & 1) * 512;
        const uint4 a = lds128(tk + hf * 2048 + o), b = lds128(tk + hf * 2048 + 1024 + o), c = k ? lds128(t3 + hf * 1024 + o) : make_uint4(0, 0, 0, 0);
        const uint32_t s0 = hadd(hadd(a.x, b.x), c.x), s1 = hadd(hadd(a.y, b.y), c.y), s2 = hadd(hadd(a.z, b.z), c.z), s3 = hadd(hadd(a.w, b.w), c.w);
        if (i < 2)
          asm volatile("st.async.weak.shared::cluster.mbarrier::complete_tx::bytes.v4.u32 [%0], {%1,%2,%3,%4}, [%5];"
                       :: "r"(mapa(sb + SM_RX + k * 1024 + lane * 16 + o, rank ^ 1)), "r"(s0), "r"(s1), "r"(s2), "r"(s3), "r"(mapa(mb + MB_RX + 8 * k, rank ^ 1)) : "memory");
        else sts128(t3 + hf * 1024 + o, s0, s1, s2, s3);
      }
      __syncwarp();
      mbar_wait(mb + MB_RX + 8 * k);
      STAMP(12);
      const int m = lane >> 3, j = lane & 7;
      const uint32_t src = (((j >> 2) == rank) ? sb + SM_T3 + k * 2048 + rank * 1024 : sb + SM_RX + k * 1024) + (j & 3) * 256;
      const uint32_t ob = sb + SM_T + k * 4096;
      #pragma unroll
      for (int it = 0; it < 4; it++) {
        const int c16 = 4 * it + m;
        uint32_t r[4];
        ldsm4t(src + ((c16 ^ (rank * 2 + (c16 >> 3)) ^ j) * 16), r);
        stsm4(ob + (it * 32 + lane) * 16, r);
      }
      fence_async();
      __syncwarp();
      if (lane == 0) {
        asm volatile("cp.async.bulk.tensor.2d.global.shared::cta.bulk_group [%0, {%2, %3}], [%1];"
                     :: "l"((uint64_t)&tmap_o), "r"(ob), "r"((cta >> 1) * 8), "r"(k * 256 + rank * 128) : "memory");
        asm volatile("cp.async.bulk.commit_group;" ::: "memory");
        asm volatile("cp.async.bulk.wait_group.read 0;" ::: "memory");
      }
      __syncwarp();
      STAMP(13);
    }
    asm volatile("barrier.cluster.arrive.relaxed.aligned;" ::: "memory");
    asm volatile("barrier.cluster.wait.aligned;" ::: "memory");
    STAMP(14);
    STAMP_DUMP();
  }
}

typedef CUresult (*EncodeFn)(CUtensorMap*, CUtensorMapDataType, cuuint32_t, void*, const cuuint64_t*, const cuuint64_t*,
                             const cuuint32_t*, const cuuint32_t*, CUtensorMapInterleave, CUtensorMapSwizzle,
                             CUtensorMapL2promotion, CUtensorMapFloatOOBfill);
}

extern "C" void kernel_launch(void* const* d_in, const int* in_sizes, int n_in, void* d_out, int out_size) {
  (void)in_sizes; (void)n_in; (void)out_size;
  static EncodeFn enc = nullptr;
  if (!enc) {
    void* fn = nullptr; cudaDriverEntryPointQueryResult qr;
    cudaGetDriverEntryPoint("cuTensorMapEncodeTiled", &fn, cudaEnableDefault, &qr);
    enc = (EncodeFn)fn;
    cudaFuncSetAttribute(ssm_gated_kernel, cudaFuncAttributeMaxDynamicSharedMemorySize, SM_TOTAL + STAMP_EXTRA);
  }
  CUtensorMap tm;
  cuuint64_t gd[2] = {(cuuint64_t)DIM, (cuuint64_t)SEQ}; cuuint64_t gs[1] = {(cuuint64_t)DIM * 2};
  cuuint32_t bd[2] = {8, 256}; cuuint32_t es[2] = {1, 1};
  enc(&tm, CU_TENSOR_MAP_DATA_TYPE_BFLOAT16, 2, d_in[0], gd, gs, bd, es, CU_TENSOR_MAP_INTERLEAVE_NONE,
      CU_TENSOR_MAP_SWIZZLE_NONE, CU_TENSOR_MAP_L2_PROMOTION_L2_128B, CU_TENSOR_MAP_FLOAT_OOB_FILL_NONE);
  CUtensorMap to;
  cuuint32_t bo[2] = {8, 128};
  enc(&to, CU_TENSOR_MAP_DATA_TYPE_BFLOAT16, 2, d_out, gd, gs, bo, es, CU_TENSOR_MAP_INTERLEAVE_NONE,
      CU_TENSOR_MAP_SWIZZLE_NONE, CU_TENSOR_MAP_L2_PROMOTION_NONE, CU_TENSOR_MAP_FLOAT_OOB_FILL_NONE);
  Params P;
  typedef const __nv_bfloat16* bp;
  P.u = (bp)d_in[0];
  const int mi[10] = {1, 2, 5, 6, 10, 11, 12, 13, 3, 4}, vi[4] = {7, 14, 8, 15};
  for (int i = 0; i < 10; i++) P.pm[i] = (bp)d_in[mi[i]];
  for (int i = 0; i < 4; i++) P.pv[i] = (bp)d_in[vi[i]];
  P.gate_w = (bp)d_in[16];
  P.out = (__nv_bfloat16*)d_out;
  ssm_gated_kernel<<<NCTA, NTHR, SM_TOTAL + STAMP_EXTRA, cudaStreamPerThread>>>(tm, to, P);
}
```

```cpp
#include <cuda_runtime.h>
#include <cuda_bf16.h>
#include <cuda_fp16.h>
#include <cuda.h>
#include <stdint.h>

#define STAMP(i) __syncwarp()
#define STAMP_EXTRA 0
#define STAMP_DUMP() do {} while (0)

namespace {

constexpr int SEQ = 2048, DIM = 512, NMODE = 128;
constexpr int NCTA = 128, NTHR = 768;

constexpr int GSLOT   = 3584;
constexpr int GBUF    = 16 * GSLOT;
constexpr int Y2_OFF = 128 * 4, Y3_OFF = (128 + 1536 + 128) * 4, Y_CH = (128 + 1536 + 128 + 1024) * 4;
constexpr int SM_G    = 0;
constexpr int SM_T    = 0;
constexpr int SM_T3   = SM_T + 32768;
constexpr int SM_Y23  = 16 * GSLOT + 1024;
constexpr int SM_RAW  = 2 * GBUF;
constexpr int SM_GW   = SM_RAW, SM_GE = SM_RAW + 10240;
constexpr int XS_CH   = 4 * 512 + 16;
constexpr int SM_XS   = SM_RAW + 16384;
constexpr int UA_ARR  = 74 * 16;
constexpr int UA_CH   = 4 * UA_ARR + 16;
constexpr int SM_RX   = SM_XS + 8320;
constexpr int SM_UA   = SM_RX + 8192;
constexpr int TW_W = 32, TW_X = 576, TW_2 = 656, TW_3 = 736, TW_TOT = 816;
constexpr int TAB_SZ  = TW_TOT * 4;
constexpr int SM_TAB  = SM_UA + 4 * UA_CH;
constexpr int SM_Y01  = SM_TAB + 8 * TAB_SZ;
constexpr int SM_ROW  = SM_Y01;
constexpr int SM_PRM  = SM_Y01 + 2 * Y_CH;
constexpr int SM_MX   = SM_PRM + 10240 + 64;
constexpr int SM_BAR  = SM_MX + 128;
constexpr int SM_TOTAL = SM_BAR + 256;
constexpr int MB_PRM = 0, MB_U = 8, MB_PEER = 16, MB_URDY = 24, MB_ROW = 32, MB_G1 = 40, MB_GW = 48, MB_G23 = 56, MB_Y = 64  , MB_LOC = 96, MB_RX = 160;
static_assert(SM_TOTAL + STAMP_EXTRA <= 232448, "smem");
static_assert(1024 + Y_CH <= 8 * GSLOT && SM_T3 + 16384 <= GBUF, "alias");
static_assert(SM_UA % 128 == 0 && SM_XS % 128 == 0 && SM_TAB % 16 == 0 && SM_Y01 % 16 == 0 && Y_CH % 16 == 0 && SM_T % 128 == 0, "align");

__device__ uint32_t g_gate[SEQ];
__device__ uint32_t g_epoch[NCTA];

struct Params {
  const __nv_bfloat16* u;
  const __nv_bfloat16* pm[10];
  const __nv_bfloat16* pv[4];
  const __nv_bfloat16* gate_w;
  __nv_bfloat16* out;
};

__device__ __forceinline__ void wgmma_n32(float* d, const uint32_t* a, uint64_t desc) {
  asm volatile("wgmma.mma_async.sync.aligned.m64n32k16.f32.bf16.bf16 {%0, %1, %2, %3, %4, %5, %6, %7, %8, %9, %10, %11, %12, %13, %14, %15}, {%16, %17, %18, %19}, %20, 1, 1, 1, 0;\n"
    : "+f"(d[0]), "+f"(d[1]), "+f"(d[2]), "+f"(d[3]), "+f"(d[4]), "+f"(d[5]), "+f"(d[6]), "+f"(d[7]), "+f"(d[8]), "+f"(d[9]), "+f"(d[10]), "+f"(d[11]), "+f"(d[12]), "+f"(d[13]), "+f"(d[14]), "+f"(d[15])
    : "r"(a[0]), "r"(a[1]), "r"(a[2]), "r"(a[3]), "l"(desc));
}

__device__ __forceinline__ void wgmma_n40(float* d, const uint32_t* a, uint64_t desc) {
  asm volatile("wgmma.mma_async.sync.aligned.m64n40k16.f32.bf16.bf16 {%0, %1, %2, %3, %4, %5, %6, %7, %8, %9, %10, %11, %12, %13, %14, %15, %16, %17, %18, %19}, {%20, %21, %22, %23}, %24, 1, 1, 1, 0;\n"
    : "+f"(d[0]), "+f"(d[1]), "+f"(d[2]), "+f"(d[3]), "+f"(d[4]), "+f"(d[5]), "+f"(d[6]), "+f"(d[7]), "+f"(d[8]), "+f"(d[9]), "+f"(d[10]), "+f"(d[11]), "+f"(d[12]), "+f"(d[13]), "+f"(d[14]), "+f"(d[15]), "+f"(d[16]), "+f"(d[17]), "+f"(d[18]), "+f"(d[19])
    : "r"(a[0]), "r"(a[1]), "r"(a[2]), "r"(a[3]), "l"(desc));
}

__device__ __forceinline__ void wgmma_n48(float* d, const uint32_t* a, uint64_t desc) {
  asm volatile("wgmma.mma_async.sync.aligned.m64n48k16.f32.bf16.bf16 {%0, %1, %2, %3, %4, %5, %6, %7, %8, %9, %10, %11, %12, %13, %14, %15, %16, %17, %18, %19, %20, %21, %22, %23}, {%24, %25, %26, %27}, %28, 1, 1, 1, 0;\n"
    : "+f"(d[0]), "+f"(d[1]), "+f"(d[2]), "+f"(d[3]), "+f"(d[4]), "+f"(d[5]), "+f"(d[6]), "+f"(d[7]), "+f"(d[8]), "+f"(d[9]), "+f"(d[10]), "+f"(d[11]), "+f"(d[12]), "+f"(d[13]), "+f"(d[14]), "+f"(d[15]), "+f"(d[16]), "+f"(d[17]), "+f"(d[18]), "+f"(d[19]), "+f"(d[20]), "+f"(d[21]), "+f"(d[22]), "+f"(d[23])
    : "r"(a[0]), "r"(a[1]), "r"(a[2]), "r"(a[3]), "l"(desc));
}

__device__ __forceinline__ void wgmma_n56(float* d, const uint32_t* a, uint64_t desc) {
  asm volatile("wgmma.mma_async.sync.aligned.m64n56k16.f32.bf16.bf16 {%0, %1, %2, %3, %4, %5, %6, %7, %8, %9, %10, %11, %12, %13, %14, %15, %16, %17, %18, %19, %20, %21, %22, %23, %24, %25, %26, %27}, {%28, %29, %30, %31}, %32, 1, 1, 1, 0;\n"
    : "+f"(d[0]), "+f"(d[1]), "+f"(d[2]), "+f"(d[3]), "+f"(d[4]), "+f"(d[5]), "+f"(d[6]), "+f"(d[7]), "+f"(d[8]), "+f"(d[9]), "+f"(d[10]), "+f"(d[11]), "+f"(d[12]), "+f"(d[13]), "+f"(d[14]), "+f"(d[15]), "+f"(d[16]), "+f"(d[17]), "+f"(d[18]), "+f"(d[19]), "+f"(d[20]), "+f"(d[21]), "+f"(d[22]), "+f"(d[23]), "+f"(d[24]), "+f"(d[25]), "+f"(d[26]), "+f"(d[27])
    : "r"(a[0]), "r"(a[1]), "r"(a[2]), "r"(a[3]), "l"(desc));
}

__device__ __forceinline__ void wgmma_n64(float* d, const uint32_t* a, uint64_t desc) {
  asm volatile("wgmma.mma_async.sync.aligned.m64n64k16.f32.bf16.bf16 {%0, %1, %2, %3, %4, %5, %6, %7, %8, %9, %10, %11, %12, %13, %14, %15, %16, %17, %18, %19, %20, %21, %22, %23, %24, %25, %26, %27, %28, %29, %30, %31}, {%32, %33, %34, %35}, %36, 1, 1, 1, 0;\n"
    : "+f"(d[0]), "+f"(d[1]), "+f"(d[2]), "+f"(d[3]), "+f"(d[4]), "+f"(d[5]), "+f"(d[6]), "+f"(d[7]), "+f"(d[8]), "+f"(d[9]), "+f"(d[10]), "+f"(d[11]), "+f"(d[12]), "+f"(d[13]), "+f"(d[14]), "+f"(d[15]), "+f"(d[16]), "+f"(d[17]), "+f"(d[18]), "+f"(d[19]), "+f"(d[20]), "+f"(d[21]), "+f"(d[22]), "+f"(d[23]), "+f"(d[24]), "+f"(d[25]), "+f"(d[26]), "+f"(d[27]), "+f"(d[28]), "+f"(d[29]), "+f"(d[30]), "+f"(d[31])
    : "r"(a[0]), "r"(a[1]), "r"(a[2]), "r"(a[3]), "l"(desc));
}

__device__ __forceinline__ uint32_t smem_u32(const void* p) { return (uint32_t)__cvta_generic_to_shared(p); }
__device__ __forceinline__ uint64_t mkdesc(uint32_t addr, uint32_t lbo, uint32_t sbo) {
  return (uint64_t)((addr & 0x3FFFF) >> 4) | ((uint64_t)(lbo >> 4) << 16) | ((uint64_t)(sbo >> 4) << 32);
}
__device__ __forceinline__ uint32_t lds32(uint32_t a) { uint32_t v; asm volatile("ld.shared.u32 %0, [%1];" : "=r"(v) : "r"(a) : "memory"); return v; }
__device__ __forceinline__ uint4 lds128(uint32_t a) { uint4 v; asm volatile("ld.shared.v4.u32 {%0,%1,%2,%3}, [%4];" : "=r"(v.x), "=r"(v.y), "=r"(v.z), "=r"(v.w) : "r"(a) : "memory"); return v; }
__device__ __forceinline__ float ldsbf(uint32_t a) { uint16_t v; asm volatile("ld.shared.u16 %0, [%1];" : "=h"(v) : "r"(a) : "memory"); return __uint_as_float((uint32_t)v << 16); }
__device__ __forceinline__ void sts16(uint32_t a, uint32_t v) { asm volatile("st.shared.u16 [%0], %1;" :: "r"(a), "h"((uint16_t)v) : "memory"); }
__device__ __forceinline__ void sts32(uint32_t a, uint32_t v) { asm volatile("st.shared.u32 [%0], %1;" :: "r"(a), "r"(v) : "memory"); }
__device__ __forceinline__ void sts128(uint32_t a, uint32_t x, uint32_t y, uint32_t z, uint32_t w) { asm volatile("st.shared.v4.u32 [%0], {%1,%2,%3,%4};" :: "r"(a), "r"(x), "r"(y), "r"(z), "r"(w) : "memory"); }
__device__ __forceinline__ void ldsm4t(uint32_t a, uint32_t* r) {
  asm volatile("ldmatrix.sync.aligned.m8n8.x4.trans.shared.b16 {%0,%1,%2,%3}, [%4];" : "=r"(r[0]), "=r"(r[1]), "=r"(r[2]), "=r"(r[3]) : "r"(a) : "memory");
}
__device__ __forceinline__ void mma_f16(float* c, const uint32_t* a, const uint32_t* b) {
  asm volatile("mma.sync.aligned.m16n8k16.row.col.f32.f16.f16.f32 {%0,%1,%2,%3}, {%4,%5,%6,%7}, {%8,%9}, {%0,%1,%2,%3};"
    : "+f"(c[0]), "+f"(c[1]), "+f"(c[2]), "+f"(c[3]) : "r"(a[0]), "r"(a[1]), "r"(a[2]), "r"(a[3]), "r"(b[0]), "r"(b[1]));
}
__device__ __forceinline__ void stsm4(uint32_t a, const uint32_t* r) {
  asm volatile("stmatrix.sync.aligned.m8n8.x4.shared.b16 [%0], {%1,%2,%3,%4};" :: "r"(a), "r"(r[0]), "r"(r[1]), "r"(r[2]), "r"(r[3]) : "memory");
}
__device__ __forceinline__ void stsm4t(uint32_t a, const uint32_t* r) {
  asm volatile("stmatrix.sync.aligned.m8n8.x4.trans.shared.b16 [%0], {%1,%2,%3,%4};" :: "r"(a), "r"(r[0]), "r"(r[1]), "r"(r[2]), "r"(r[3]) : "memory");
}
__device__ __forceinline__ void mma_bf16(float* c, uint32_t a0, uint32_t a1, uint32_t a2, uint32_t a3, const uint32_t* b) {
  asm volatile("mma.sync.aligned.m16n8k16.row.col.f32.bf16.bf16.f32 {%0,%1,%2,%3}, {%4,%5,%6,%7}, {%8,%9}, {%0,%1,%2,%3};"
    : "+f"(c[0]), "+f"(c[1]), "+f"(c[2]), "+f"(c[3]) : "r"(a0), "r"(a1), "r"(a2), "r"(a3), "r"(b[0]), "r"(b[1]));
}
__device__ __forceinline__ void bar_sync(int id, int n) { asm volatile("bar.sync %0, %1;" :: "r"(id), "r"(n) : "memory"); }
__device__ __forceinline__ void bar_arrive(int id, int n) { asm volatile("bar.arrive %0, %1;" :: "r"(id), "r"(n) : "memory"); }
__device__ __forceinline__ float ex2f(float x) { float y; asm("ex2.approx.ftz.f32 %0, %1;" : "=f"(y) : "f"(x)); return y; }
__device__ __forceinline__ float sinaf(float x) { float y; asm("sin.approx.ftz.f32 %0, %1;" : "=f"(y) : "f"(x)); return y; }
__device__ __forceinline__ float cosaf(float x) { float y; asm("cos.approx.ftz.f32 %0, %1;" : "=f"(y) : "f"(x)); return y; }
__device__ __forceinline__ uint32_t pack_h2(float lo, float hi) { uint32_t r; asm("cvt.rn.f16x2.f32 %0, %1, %2;" : "=r"(r) : "f"(hi), "f"(lo)); return r; }
__device__ __forceinline__ uint32_t pack_bf2(float lo, float hi) { uint32_t r; asm("cvt.rn.bf16x2.f32 %0, %1, %2;" : "=r"(r) : "f"(hi), "f"(lo)); return r; }
__device__ __forceinline__ float bf_lo(uint32_t v) { return __uint_as_float(v << 16); }
__device__ __forceinline__ float bf_hi(uint32_t v) { return __uint_as_float(v & 0xffff0000u); }
__device__ __forceinline__ float bf16_round(float x) { return __bfloat162float(__float2bfloat16_rn(x)); }
__device__ __forceinline__ uint32_t hadd(uint32_t a, uint32_t b) { __nv_bfloat162 r = __hadd2(*(__nv_bfloat162*)&a, *(__nv_bfloat162*)&b); return *(uint32_t*)&r; }
__device__ __forceinline__ float exp_acc(float x) {
  const float L = 1.4426950408889634f, Ll = 1.9259629911266175e-8f;
  float t = x * L, r = fmaf(x, L, -t); r = fmaf(x, Ll, r);
  return ex2f(t) * fmaf(r, 0.6931471805599453f, 1.f);
}
__device__ __forceinline__ void mbar_init(uint32_t a, int n) { asm volatile("mbarrier.init.shared.b64 [%0], %1;" :: "r"(a), "r"(n)); }
__device__ __forceinline__ void mbar_arrive(uint32_t a) { asm volatile("mbarrier.arrive.shared.b64 _, [%0];" :: "r"(a) : "memory"); }
__device__ __forceinline__ void mbar_expect(uint32_t a, int bytes) { asm volatile("mbarrier.arrive.expect_tx.shared.b64 _, [%0], %1;" :: "r"(a), "r"(bytes) : "memory"); }
__device__ __forceinline__ void mbar_wait(uint32_t a) {
  uint32_t ok = 0; int it = 0;
  while (!ok && it++ < (1 << 20))
    asm volatile("{ .reg .pred p; mbarrier.try_wait.parity.shared.b64 p, [%1], 0, 2000; selp.u32 %0, 1, 0, p; }" : "=r"(ok) : "r"(a) : "memory");
}
__device__ __forceinline__ void warp_arrive(uint32_t a, int lane) { __syncwarp(); if (lane == 0) mbar_arrive(a); }
__device__ __forceinline__ void fence_async() { asm volatile("fence.proxy.async.shared::cta;" ::: "memory"); }
__device__ __forceinline__ uint32_t mapa(uint32_t a, uint32_t rank) { uint32_t r; asm("mapa.shared::cluster.u32 %0, %1, %2;" : "=r"(r) : "r"(a), "r"(rank)); return r; }
__device__ __forceinline__ void dsmem_copy(uint32_t dst, uint32_t src, int bytes, uint32_t mb) {
  asm volatile("cp.async.bulk.shared::cluster.shared::cta.mbarrier::complete_tx::bytes [%0], [%1], %2, [%3];" :: "r"(dst), "r"(src), "r"(bytes), "r"(mb) : "memory");
}
__device__ __forceinline__ void bulk_g2s(uint32_t dst, const void* src, int bytes, uint32_t mb) {
  asm volatile("cp.async.bulk.shared::cluster.global.mbarrier::complete_tx::bytes [%0], [%1], %2, [%3];" :: "r"(dst), "l"(src), "r"(bytes), "r"(mb) : "memory");
}
__device__ __forceinline__ void wg_fence() { asm volatile("wgmma.fence.sync.aligned;" ::: "memory"); }
__device__ __forceinline__ void wg_commit() { asm volatile("wgmma.commit_group.sync.aligned;" ::: "memory"); }
template <int N> __device__ __forceinline__ void wg_wait() { asm volatile("wgmma.wait_group.sync.aligned %0;" :: "n"(N) : "memory"); }
template <int N> __device__ __forceinline__ void fence_acc(float* d) {
  #pragma unroll
  for (int i = 0; i < N; i++) asm volatile("" : "+f"(d[i]) :: "memory");
}

struct cf { float x, y; };
__device__ __forceinline__ cf cmul(cf a, cf b) { cf r; r.x = a.x * b.x - a.y * b.y; r.y = a.x * b.y + a.y * b.x; return r; }
__device__ __forceinline__ cf cmulc(cf a, cf b) { cf r; r.x = a.x * b.x + a.y * b.y; r.y = a.y * b.x - a.x * b.y; return r; }
__device__ __forceinline__ cf csq(cf a) { cf r; r.x = a.x * a.x - a.y * a.y; r.y = (a.x + a.x) * a.y; return r; }
__device__ __forceinline__ cf cexp_fast(float a2, float th, float x) {
  float e = ex2f(a2 * x), ph = th * x; cf r; r.x = e * cosaf(ph); r.y = e * sinaf(ph); return r;
}
struct hp { uint32_t r, i; };
__device__ __forceinline__ hp hbro(cf m) { hp h; h.r = pack_h2(m.x, m.x); h.i = pack_h2(m.y, m.y); return h; }
template <bool CONJ> __device__ __forceinline__ hp hmul(hp a, hp m) {
  const __half2 ar = *(__half2*)&a.r, ai = *(__half2*)&a.i, mr = *(__half2*)&m.r, mi = CONJ ? __hneg2(*(__half2*)&m.i) : *(__half2*)&m.i;
  const __half2 x = __hfma2(ar, mr, __hneg2(__hmul2(ai, mi))), y = __hfma2(ar, mi, __hmul2(ai, mr));
  hp o; o.r = *(uint32_t*)&x; o.i = *(uint32_t*)&y; return o;
}
__device__ __forceinline__ hp hlo(hp a, hp b) { hp o; o.r = __byte_perm(a.r, b.r, 0x5410); o.i = __byte_perm(a.i, b.i, 0x5410); return o; }
__device__ __forceinline__ void put4(uint32_t a, hp p0, hp p1, hp p2, hp p3) {
  sts128(a, p0.r, p1.r, p2.r, p3.r); sts128(a + 128, p0.i, p1.i, p2.i, p3.i);
}

struct Pow { hp t0, z, m2, m4, m256, m512, m1024, b0, m16, m32; uint32_t m64, m128; };
__device__ __forceinline__ void gen_powers(Pow& p, float al, float tt, cf c) {
  const cf w1 = cexp_fast(al, tt, 1.f), w64 = cexp_fast(al, tt, 64.f);
  const cf w2 = csq(w1), w4 = csq(w2), w8 = csq(w4), w16 = csq(w8), w32 = csq(w16);
  const cf w128 = csq(w64), w256 = csq(w128), w512 = csq(w256), w1024 = csq(w512);
  const cf c1 = cmulc(c, w1), c512 = cmulc(c, w512), c768 = cmulc(c512, w256);
  p.t0.r = pack_h2(c.x, c1.x); p.t0.i = pack_h2(c.y, c1.y);
  p.z.r = pack_h2(c512.x, c768.x); p.z.i = pack_h2(c512.y, c768.y);
  p.m2 = hbro(w2); p.m4 = hbro(w4); p.m256 = hbro(w256); p.m512 = hbro(w512); p.m1024 = hbro(w1024);
  p.b0.r = pack_h2(1.f, w8.x); p.b0.i = pack_h2(0.f, w8.y);
  p.m16 = hbro(w16); p.m32 = hbro(w32); p.m64 = pack_h2(w64.x, w64.y); p.m128 = pack_h2(w128.x, w128.y);
}
constexpr int KSLOT = 1024;
__device__ __forceinline__ void gen_store(const Pow& p, uint32_t gb, uint32_t gm) {
  const uint32_t bb = gb + 256;
  hp t1 = hmul<true>(p.t0, p.m2), t2 = hmul<true>(p.t0, p.m4), t3 = hmul<true>(t1, p.m4);
  put4(bb, p.t0, t1, t2, t3);
  const hp z4 = hmul<true>(p.z, p.m4);
  hp u0, u1; u0.r = __byte_perm(p.z.r, z4.r, 0x5410); u0.i = __byte_perm(p.z.i, z4.i, 0x5410);
  u1.r = __byte_perm(p.z.r, z4.r, 0x7632); u1.i = __byte_perm(p.z.i, z4.i, 0x7632);
  put4(bb + 256, hmul<true>(hlo(p.t0, t1), p.m256), hmul<true>(hlo(t2, t3), p.m256), u0, u1);
  u0 = hmul<true>(p.z, p.m512); u1 = hmul<true>(p.z, p.m1024);
  const hp u2 = hmul<true>(u0, p.m1024);
  put4(bb + 512, u0, u1, u2, u2);
  t1 = hmul<false>(p.b0, p.m16); t2 = hmul<false>(p.b0, p.m32); t3 = hmul<false>(t1, p.m32);
  put4(gb, p.b0, t1, t2, t3);
  sts16(gm, p.m64); sts16(gm + 4, p.m64 >> 16); sts16(gm + 128, p.m128); sts16(gm + 132, p.m128 >> 16);
  __syncwarp();
}
__device__ __forceinline__ void gen_contract(float* d, uint32_t la, uint32_t lb, uint32_t lm, uint32_t zr) {
  #pragma unroll
  for (int ks = 0; ks < 4; ks++) {
    uint32_t fa[4], fc[4], fb[8];
    ldsm4t(la + ks * KSLOT, fb + 4);
    hp m64, m128, x, y;
    asm volatile("ld.shared.v2.u32 {%0,%1}, [%2];" : "=r"(m64.r), "=r"(m64.i) : "r"(lm + ks * 32) : "memory");
    asm volatile("ld.shared.v2.u32 {%0,%1}, [%2];" : "=r"(m128.r), "=r"(m128.i) : "r"(lm + ks * 32 + 128) : "memory");
    ldsm4t(lb + ks * KSLOT, fb);
    x.r = fb[6]; x.i = fb[7]; y = hmul<false>(x, m64);
    fa[0] = x.r + zr; fa[2] = x.i + zr; fa[1] = y.r; fa[3] = y.i;
    x = hmul<false>(x, m128); y = hmul<false>(y, m128);
    fc[0] = x.r; fc[2] = x.i; fc[1] = y.r; fc[3] = y.i;
    #pragma unroll
    for (int nt = 0; nt < 3; nt++) { mma_f16(d + 4 * nt, fa, fb + 2 * nt); mma_f16(d + 12 + 4 * nt, fc, fb + 2 * nt); }
  }
  __syncwarp();
}

template <int S> __device__ __forceinline__ void near_step(float* d, uint64_t ud, const uint32_t* a) {
  constexpr int arr = (S & 1) ? 0 : 2;
  constexpr int slot = (S & 1) ? (S - 1) / 2 : S / 2;
  const uint64_t desc = ud + (uint64_t)((arr * UA_ARR + slot * 16) >> 4);
  if constexpr (S < 16) wgmma_n64(d, a, desc);
  else if constexpr (S < 32) wgmma_n56(d, a, desc);
  else if constexpr (S < 34) wgmma_n48(d, a, desc);
  else if constexpr (S == 63) wgmma_n40(d, a, desc);
  else wgmma_n32(d, a, desc);
}
template <int S0, int NS> __device__ __forceinline__ void near_load(uint32_t (*a)[4], uint32_t wa, uint32_t zr) {
  a[0][2] = lds32(wa + (uint32_t)((2 * S0 - 1) * 32));
  #pragma unroll
  for (int i = 0; i < NS; i++) {
    a[i][0] = lds32(wa + (2 * (S0 + i)) * 32);
    a[i][1] = lds32(wa + (2 * (S0 + i) + 1) * 32);
  }
  #pragma unroll
  for (int i = 0; i < NS; i++) {
    a[i][3] = a[i][0] + zr;
    if (i + 1 < NS) a[i + 1][2] = a[i][1] + zr;
  }
}
template <int S0, int NS> __device__ __forceinline__ void near_issue(float* d, uint64_t ua, uint32_t (*a)[4]) {
  wg_fence();
  near_step<S0>(d, ua, a[0]);
  if constexpr (NS > 1) near_step<S0 + 1>(d, ua, a[1]);
  if constexpr (NS > 2) near_step<S0 + 2>(d, ua, a[2]);
  if constexpr (NS > 3) near_step<S0 + 3>(d, ua, a[3]);
  if constexpr (NS > 4) near_step<S0 + 4>(d, ua, a[4]);
  if constexpr (NS > 5) near_step<S0 + 5>(d, ua, a[5]);
  wg_commit();
}

__device__ __forceinline__ void sts2x(uint32_t o, const uint32_t* w) {
  const bool sw = (threadIdx.x >> 2) & 1;
  sts128(o + (sw ? 16 : 0), sw ? w[4] : w[0], sw ? w[5] : w[1], sw ? w[6] : w[2], sw ? w[7] : w[3]);
  sts128(o + (sw ? 0 : 16), sw ? w[0] : w[4], sw ? w[1] : w[5], sw ? w[2] : w[6], sw ? w[3] : w[7]);
}
__device__ __forceinline__ void ytab_chunk(uint32_t ub, uint32_t yb, int chi) {
  auto ca = [&](int c) { return ub + (c & 3) * UA_ARR - (c >> 2) * 16; };
  const uint4 z = lds128(ca(chi - 2)), a = lds128(ca(chi - 1)), b = lds128(ca(chi)), c = lds128(ca(chi + 1));
  const float v[23] = {bf_hi(z.z), bf_lo(z.w), bf_hi(z.w),
                       bf_lo(a.x), bf_hi(a.x), bf_lo(a.y), bf_hi(a.y), bf_lo(a.z), bf_hi(a.z), bf_lo(a.w), bf_hi(a.w),
                       bf_lo(b.x), bf_hi(b.x), bf_lo(b.y), bf_hi(b.y), bf_lo(b.z), bf_hi(b.z), bf_lo(b.w), bf_hi(b.w),
                       bf_lo(c.x), bf_hi(c.x), bf_lo(c.y), bf_hi(c.y)};
  float s[24];
  s[13] = 0.f; s[14] = v[13]; s[12] = -v[12];
  #pragma unroll
  for (int i = 15; i < 24; i++) s[i] = s[i - 1] + v[i - 1];
  #pragma unroll
  for (int i = 11; i >= 0; i--) s[i] = s[i + 1] - v[i];
  uint32_t w[8];
  {
    #pragma unroll
    for (int i = 0; i < 8; i++) w[i] = pack_bf2(s[i + 14] - s[i + 9], s[i + 9] - s[i + 6]);
    const int cp = (chi ^ ((chi >> 2) & 1)) * 32;
    uint32_t o = yb + Y2_OFF + cp;
    sts2x(o, w);
    if (chi < 128) {
      #pragma unroll
      for (int i = 0; i < 8; i++) w[i] = pack_bf2(s[i + 16] - s[i + 7], s[i + 7] - s[i]);
      o = yb + Y3_OFF + cp;
      sts2x(o, w);
    }
  }
}

__device__ __forceinline__ uint32_t ldv32(uint32_t a) { uint32_t v; asm volatile("ld.volatile.shared.u32 %0, [%1];" : "=r"(v) : "r"(a) : "memory"); return v; }
__device__ __forceinline__ void ld_frag(uint32_t* n, uint32_t x, int dp, int dm) { n[0] = ldv32(x); n[1] = ldv32(x + dp); n[2] = ldv32(x + dm); }
__device__ __forceinline__ void far_octet(float (*acc)[4], int j0, uint32_t yb, uint32_t kb, int g, int q, const uint32_t (*b2)[2]) {
  const int mu = g >> 1;
  const uint32_t zr = ldv32(kb);
  uint32_t a[4][4];
  const int dp = q < 2 ? -32 : 32;
  if (j0 >= 4) {
    const uint32_t ya = yb + Y2_OFF + (64 * (j0 - 8) + 48 - 16 * q + (q < 2 ? 8 : 0) + g) * 4;
    const int dm = (q == 0) ? -96 : (q == 2) ? -32 : -64;
    #pragma unroll
    for (int i = 0; i < 3; i++) ld_frag(a[i], ya + (3 - i) * 256, dp, dm);
    #pragma unroll
    for (int i = 0; i < 12; i++) {
      const int br = 3 - i;
      if ((i & 3) == 1 && j0 + br < 7) break;
      if (i + 3 < 12) ld_frag(a[(i + 3) & 3], ya + (br - 3) * 256, dp, dm);
      uint32_t* c = a[i & 3];
      c[3] = c[0] + zr;
      #pragma unroll
      for (int j = 0; j < 4; j++) { const int s = j - br; if (s >= 0 && s < 9) mma_bf16(acc[j], c[0], c[1], c[2], c[3], b2[s]); }
    }
  }
  if (j0 >= 12) {
    const uint32_t ya = yb + Y3_OFF + (64 * (j0 - 16) + 48 - 16 * q + (q < 2 ? 8 : 0) + g) * 4;
    #pragma unroll
    for (int i = 0; i < 3; i++) { a[i][0] = ldv32(ya + (3 - i) * 256); a[i][1] = ldv32(ya + (3 - i) * 256 + dp); }
    uint32_t b3[9][2];
    #pragma unroll
    for (int s = 0; s < 9; s++) { b3[s][0] = ldv32(kb + (TW_3 + mu + q + 8 * s) * 4); b3[s][1] = ldv32(kb + (TW_3 + mu + q + 8 * s + 4) * 4); }
    #pragma unroll
    for (int i = 0; i < 17; i++) {
      const int br = 3 - i;
      if ((i & 3) == 1 && j0 + br < 15) break;
      if (i + 3 < 18) { uint32_t* n = a[(i + 3) & 3]; n[0] = ldv32(ya + (br - 3) * 256); n[1] = ldv32(ya + (br - 3) * 256 + dp); }
      uint32_t* c = a[i & 3];
      c[2] = a[(i + 1) & 3][0] + zr; c[3] = a[(i + 1) & 3][1] + zr;
      #pragma unroll
      for (int j = 0; j < 4; j++) { const int s2 = j - br; if (s2 >= 0 && !(s2 & 1)) mma_bf16(acc[j], c[0], c[1], c[2], c[3], b3[s2 >> 1]); }
    }
  }
}

__global__ void __cluster_dims__(2, 1, 1) __launch_bounds__(NTHR, 1)
ssm_gated_kernel(const __grid_constant__ CUtensorMap tmap_u, const __grid_constant__ CUtensorMap tmap_o, const __grid_constant__ Params P) {
  extern __shared__ __align__(1024) unsigned char smem[];
  const uint32_t sb = smem_u32(smem);
  const int tid = threadIdx.x, warp = __shfl_sync(~0u, tid >> 5, 0), lane = tid & 31;
  const int g = lane >> 2, q = lane & 3;
  const int cta = blockIdx.x, c0 = cta * 4, rank = cta & 1;
  const uint32_t mb = sb + SM_BAR;
  if (tid == 0) {
    mbar_init(mb + MB_PRM, 1); mbar_init(mb + MB_ROW, 1);
    fence_async();
    mbar_expect(mb + MB_PRM, 10240 + 64);
    #pragma unroll
    for (int i = 0; i < 10; i++) bulk_g2s(sb + SM_PRM + i * 1024, P.pm[i] + c0 * NMODE, 1024, mb + MB_PRM);
    #pragma unroll
    for (int i = 0; i < 4; i++) bulk_g2s(sb + SM_PRM + 10240 + i * 16, P.pv[i] + (cta >> 1) * 8, 16, mb + MB_PRM);
  }
  if (tid == 32) {
    mbar_init(mb + MB_U, 1); mbar_init(mb + MB_URDY, 1);
    mbar_init(mb + MB_G1, 8); mbar_init(mb + MB_G23, 8); mbar_init(mb + MB_PEER, 1); mbar_init(mb + MB_GW, 4);
    #pragma unroll
    for (int i = 0; i < 4; i++) mbar_init(mb + MB_Y + 8 * i, 8);
    #pragma unroll
    for (int i = 0; i < 8; i++) { mbar_init(mb + MB_LOC + 8 * i, i ? 20 : 16); mbar_init(mb + MB_RX + 8 * i, 1); }
    asm volatile("fence.mbarrier_init.release.cluster;" ::: "memory");
    fence_async();
  }
  STAMP(0);

  if (warp < 16) {
    const int ch = warp >> 2, br = (warp >> 1) & 1, w0 = warp & 1;
    asm volatile("setmaxnreg.inc.sync.aligned.u32 96;");
    for (int i = tid; i < (SM_Y01 - SM_TAB) / 16; i += 512) sts128(sb + SM_TAB + i * 16, 0, 0, 0, 0);
    if (tid < 160) sts128(sb + SM_UA + (tid / 40) * UA_CH + ((tid / 10) & 3) * UA_ARR + (64 + tid % 10) * 16, 0, 0, 0, 0);
    fence_async();
    asm volatile("barrier.cluster.arrive.relaxed.aligned;" ::: "memory");
    bar_sync(0, NTHR);
    const uint32_t tab = sb + SM_TAB + (ch * 2 + br) * TAB_SZ;
    const int pb = (warp >> 1) < 5 ? 6 + (warp >> 1) : 8 + (warp >> 1);
    const uint32_t zr = lds32(tab);
    const uint32_t yb = sb + (ch < 2 ? SM_Y01 + ch * Y_CH : SM_Y23 + (ch - 2) * 8 * GSLOT);
    {
      const uint32_t gw = sb + SM_G + warp * (2 * GSLOT);
      const uint32_t gb = gw + (lane >> 3) * KSLOT + (lane & 7) * 16;
      const uint32_t gm = gw + 4 * KSLOT + (lane >> 1) * 8 + (lane & 1) * 2;
      const uint32_t la = gw + (((lane >> 3) * 128 + 768) & 1023) + (lane & 7) * 16;
      const uint32_t lb = gw + 256 + (lane >> 3) * 128 + (lane & 7) * 16;
      const uint32_t lm = gw + 4 * KSLOT + q * 8;
      float a2[2], th[2]; cf cc[2];
      const uint32_t pp = sb + SM_PRM + br * 4096 + ch * 256 + (w0 * 32 + lane) * 4;
      const uint32_t pl = sb + SM_PRM + 10240 + br * 16 + rank * 8 + ch * 2;
      mbar_wait(mb + MB_PRM);
      STAMP(1);
      const uint32_t q0 = lds32(pp), q1 = lds32(pp + 1024), q2 = lds32(pp + 2048), q3 = lds32(pp + 3072);
      uint32_t q4 = 0x40004000u, q5 = 0;
      if (!br) { q4 = lds32(pp + 8192); q5 = lds32(pp + 9216); }
      const float dt = bf16_round(exp_acc(ldsbf(pl)));
      float mxf = 0.f;
      #pragma unroll
      for (int r = 0; r < 2; r++) {
        float are = r ? bf_hi(q0) : bf_lo(q0);
        if (br) are = -bf16_round(exp_acc(are));
        a2[r] = (are * dt) * 1.4426950408889634f; th[r] = (r ? bf_hi(q1) : bf_lo(q1)) * dt;
        cf c = {r ? bf_hi(q2) : bf_lo(q2), r ? bf_hi(q3) : bf_lo(q3)};
        const cf dB = {dt * (r ? bf_hi(q4) : bf_lo(q4)), dt * (r ? bf_hi(q5) : bf_lo(q5))};
        c = cmul(c, dB); cc[r].x = c.x; cc[r].y = -c.y;
        mxf = fmaxf(mxf, fmaxf(fabsf(c.x), fabsf(c.y)));
      }
      const int e = min(max((int)(__reduce_max_sync(~0u, __float_as_uint(mxf)) >> 23), 1), 252);
      const float sc = __uint_as_float((uint32_t)(253 - e) << 23);
      float d[24];
      #pragma unroll
      for (int i = 0; i < 24; i++) d[i] = 0.f;
      {
        Pow p;
        cf c = cc[0]; c.x *= sc; c.y *= sc;
        gen_powers(p, a2[0], th[0], c);
        if (ch >= 2) bar_sync(5, 512);
        gen_store(p, gb, gm);
        if (ch < 2) bar_arrive(5, 512);
        STAMP(2);
        c = cc[1]; c.x *= sc; c.y *= sc;
        gen_powers(p, a2[1], th[1], c);
        gen_contract(d, la, lb, lm, zr);
        gen_store(p, gb, gm);
        STAMP(3);
        gen_contract(d, la, lb, lm, zr);
      }
      const float isc = __uint_as_float((uint32_t)(e + 1) << 23);
      const int jr = w0 * 16 + g;
      const uint32_t a0 = tab + (TW_W + 8 * jr + 2 * q) * 4;
      const uint32_t a1 = tab + (q < 2 ? TW_W + 256 + 8 * jr + 4 * q : TW_2 + 6 + 32 * (q - 2) + jr) * 4;
      const uint32_t a3 = tab + TW_3 * 4 + (6 + 64 * q + jr) * 2;
      float k[12];
      {
        #pragma unroll
        for (int i = 0; i < 3; i++) {
          sts128(gw + i * 512 + lane * 16, __float_as_uint((w0 ? d[4 * i] : d[12 + 4 * i]) * isc), __float_as_uint((w0 ? d[4 * i + 1] : d[13 + 4 * i]) * isc),
                 __float_as_uint((w0 ? d[4 * i + 2] : d[14 + 4 * i]) * isc), __float_as_uint((w0 ? d[4 * i + 3] : d[15 + 4 * i]) * isc));
        }
        const float own = (lane == 0 ? d[8] : d[4]) * isc;
        if (!w0 && (lane == 0 || lane == 2)) sts32(gw + 1536 + lane * 2, __float_as_uint(own));
        const float fo = __shfl_sync(~0u, own, q == 3 ? 0 : 2);
        bar_sync(pb, 64);
        const uint32_t po = sb + SM_G + (warp ^ 1) * (2 * GSLOT) + lane * 16;
        #pragma unroll
        for (int i = 0; i < 3; i++) {
          const uint4 v = lds128(po + i * 512);
          k[4 * i]     = fmaf(w0 ? d[12 + 4 * i] : d[4 * i], isc, __uint_as_float(v.x));
          k[4 * i + 1] = fmaf(w0 ? d[13 + 4 * i] : d[4 * i + 1], isc, __uint_as_float(v.y));
          k[4 * i + 2] = fmaf(w0 ? d[14 + 4 * i] : d[4 * i + 2], isc, __uint_as_float(v.z));
          k[4 * i + 3] = fmaf(w0 ? d[15 + 4 * i] : d[4 * i + 3], isc, __uint_as_float(v.w));
        }
        if (w0 && g == 7 && (q & 1)) k[7] -= fo + __uint_as_float(lds32(po - lane * 16 + 1536 + (q == 3 ? 0 : 4)));
        warp_arrive(mb + (ch < 2 ? MB_G1 : MB_G23), lane);
      }
      if (jr == 0 && q == 0) k[0] += ldsbf(pl + 32);
      #pragma unroll
      for (int h = 0; h < 2; h++) {
        uint32_t w = pack_bf2(k[2 * h + 1], k[2 * h]);
        sts16(a0 + h * 256, w >> 16); sts32(a0 + h * 256 + 4, w); sts16(a0 + h * 256 + 10, w);
        w = pack_bf2(k[4 + 2 * h], k[5 + 2 * h]);
        if (q < 2) {
          const uint32_t a = a1 + h * 256, w0w = __byte_perm(w, w, 0x1010);
          if (h == 0 && jr == 0 && q == 0) sts16(a, w0w); else { sts16(a - 4, w0w); sts32(a, w0w); }
          sts32(a + 4, w0w); sts32(a + 8, __byte_perm(w, w, 0x1032)); sts16(a + 14, w >> 16);
        } else sts32(a1 + h * 32, w);
        w = pack_bf2(k[8 + 2 * h], k[9 + 2 * h]);
        if (q < 2 || (q == 2 && h == 0 && jr == 0)) sts16(a3 + h * 16, w);
        if (q < 2) sts16(a3 + h * 16 + 64, w >> 16);
        if (h == 0 && jr == 0 && q == 0) { sts16(tab + (TW_X + 1019 - 976) * 4, w); sts16(tab + (TW_X + 1020 - 976) * 4 + 2, w); }
      }
      bar_sync(pb, 64);
      STAMP(4);
    }
    {
      const uint64_t ua = mkdesc(sb + SM_UA + ch * UA_CH, UA_ARR, 128);
      const uint32_t wa = tab + (TW_W + 16 * w0 + g - 2 * q - 16) * 4;
      float d[32];
      #pragma unroll
      for (int i = 0; i < 32; i++) d[i] = 0.f;
      uint32_t A[4][4], B[4][4];
      near_load<0, 4>(A, wa, zr);
      near_load<4, 4>(B, wa, zr);
      STAMP(6);
      mbar_wait(mb + MB_URDY);
      STAMP(7);
      fence_acc<32>(d);
      near_issue<0, 4>(d, ua, A);
      near_issue<4, 4>(d, ua, B);   wg_wait<1>();
      near_load<8, 4>(A, wa, zr);   near_issue<8, 4>(d, ua, A);   wg_wait<1>();
      near_load<12, 4>(B, wa, zr);  near_issue<12, 4>(d, ua, B);  wg_wait<1>();
      near_load<16, 4>(A, wa, zr);
      wg_wait<0>();
      fence_acc<32>(d);
      bar_sync(1 + ch, 128);
      mbar_wait(mb + MB_GW);
      mbar_wait(mb + MB_G1);
      int ln; asm volatile("mov.u32 %0, %%laneid;" : "=r"(ln));
      const int m = ln >> 3, tl = 7 - (ln & 7);
      const uint32_t ga = sb + SM_GW + br * 5120 + ((3 - (ln & 3)) * 40 + 16 * w0 + (ln >> 2)) * 4;
      const int c16 = 4 * (tl & 3) + 2 * w0 + (m & 1);
      const uint32_t ta = sb + SM_T + (m >> 1) * 4096 + (tl >> 2) * 2048 + (br * 4 + ch) * 256 + ((c16 ^ (tl >> 1) ^ (rank * 4 + ch)) * 16);
      {
        uint32_t r[2];
        #pragma unroll
        for (int h = 0; h < 2; h++) {
          const uint32_t gw = lds32(ga + 8 * h * 4), y = pack_bf2(d[28 + 2 * h], d[29 + 2 * h]);
          const __nv_bfloat162 t2 = __hmul2(*(const __nv_bfloat162*)&y, *(const __nv_bfloat162*)&gw);
          r[h] = *(const uint32_t*)&t2;
        }
        asm volatile("stmatrix.sync.aligned.m8n8.x2.trans.shared.b16 [%0], {%1,%2};" :: "r"(ta), "r"(r[0]), "r"(r[1]) : "memory");
        warp_arrive(mb + MB_LOC, lane);
      }
      fence_acc<28>(d);
      near_issue<16, 4>(d, ua, A);
      near_load<20, 4>(B, wa, zr);  near_issue<20, 4>(d, ua, B);  wg_wait<1>();
      near_load<24, 4>(A, wa, zr);  near_issue<24, 4>(d, ua, A);  wg_wait<1>();
      near_load<28, 4>(B, wa, zr);  near_issue<28, 4>(d, ua, B);  wg_wait<1>();
      near_load<32, 2>(A, wa, zr);  near_issue<32, 2>(d, ua, A);  wg_wait<1>();
      near_load<63, 3>(B, wa - (uint32_t)((976 + TW_W - TW_X) * 4), zr);
      near_issue<63, 1>(d, ua, B);
      near_issue<64, 2>(d, ua, B + 1);
      wg_wait<0>();
      fence_acc<28>(d);
      STAMP(8);
      #pragma unroll
      for (int i = 1; i < 8; i += 2) {
        uint32_t r[4];
        #pragma unroll
        for (int kk = 0; kk < (i < 7 ? 4 : 2); kk++) {
          const int ii = i + (kk >> 1), h = kk & 1;
          const uint32_t gw = lds32(ga + (ii * 160 + 8 * h) * 4);
          const uint32_t y = pack_bf2(d[4 * (7 - ii) + 2 * h], d[4 * (7 - ii) + 2 * h + 1]);
          const __nv_bfloat162 t2 = __hmul2(*(const __nv_bfloat162*)&y, *(const __nv_bfloat162*)&gw);
          r[kk] = *(const uint32_t*)&t2;
        }
        if (i < 7) stsm4t(ta + i * 4096, r);
        else asm volatile("stmatrix.sync.aligned.m8n8.x2.trans.shared.b16 [%0], {%1,%2};" :: "r"(ta + i * 4096 - (m >> 1) * 4096), "r"(r[0]), "r"(r[1]) : "memory");
        __syncwarp();
        if (lane < (i < 7 ? 2 : 1)) mbar_arrive(mb + MB_LOC + 8 * (i + lane));
      }
    }
    STAMP(9);
    {
      int lane; asm volatile("mov.u32 %0, %%laneid;" : "=r"(lane));
      const int g = lane >> 2, q = lane & 3;
      const uint32_t kb = sb + SM_TAB + (ch * 2 + (g & 1)) * TAB_SZ;
      uint32_t b2[9][2];
      #pragma unroll
      for (int s = 0; s < 9; s++)
        asm volatile("ld.shared.v2.u32 {%0,%1}, [%2];" : "=r"(b2[s][0]), "=r"(b2[s][1]) : "r"(kb + (TW_2 + 2 * (g >> 1) + 2 * q + 8 * s) * 4) : "memory");
      mbar_wait(mb + MB_Y + 8 * ch);
      STAMP(10);
      const int c32 = lane, c16 = c32 & 15;
      const uint32_t t3a = sb + SM_T3 + (c32 >> 4) * 1024 + ch * 256 + ((c16 ^ (c32 >> 3) ^ (rank * 4 + ch)) * 16);
      #pragma unroll 1
      for (int ps = 0; ps < 2; ps++) {
        const int o4 = (warp + ch) & 3, oc = ps ? o4 + 4 : o4, j0 = 4 * oc;
        if (oc == 0) continue;
        float acc[4][4];
        uint32_t gq[4];
        #pragma unroll
        for (int j = 0; j < 4; j++) {
          gq[j] = lds32(sb + SM_GE + (32 * (j0 + j) + 8 * q + g) * 4);
          acc[j][0] = acc[j][1] = acc[j][2] = acc[j][3] = 0.f;
        }
        far_octet(acc, j0, yb, kb, g, q, b2);
        uint32_t r[4];
        #pragma unroll
        for (int j = 0; j < 4; j++)
          r[j] = pack_bf2(fmaf(bf_lo(gq[j]), acc[j][0] - acc[j][1], acc[j][1]), fmaf(bf_hi(gq[j]), acc[j][2] - acc[j][3], acc[j][3]));
        stsm4t(t3a + oc * 2048, r);
        warp_arrive(mb + MB_LOC + 8 * oc, lane);
        STAMP(11 + ps);
      }
    }
  } else {
    asm volatile("setmaxnreg.dec.sync.aligned.u32 48;");
    const int aw = warp - 16, at = tid - 512;
    const uint32_t epoch = __ldcg(&g_epoch[cta]) + 1u, tag = epoch & 0xffffu;
    asm volatile("barrier.cluster.arrive.relaxed.aligned;" ::: "memory");
    bar_sync(0, NTHR);
    STAMP(1);
    if (aw >= 4) {
      const int bw = aw - 4, bt = at - 128;
      if (bt == 0) {
        mbar_expect(mb + MB_ROW, 16384 + 1024);
        bulk_g2s(sb + SM_ROW, P.u + (size_t)cta * 16 * DIM, 16384, mb + MB_ROW);
        bulk_g2s(sb + SM_ROW + 16384, P.gate_w, 1024, mb + MB_ROW);
        mbar_expect(mb + MB_U, 16384);
        #pragma unroll
        for (int i = 0; i < 4; i++)
          asm volatile("cp.async.bulk.tensor.2d.shared::cluster.global.mbarrier::complete_tx::bytes [%0], [%1, {%3, %4}], [%2];"
                       :: "r"(sb + SM_RAW + i * 4096), "l"((uint64_t)&tmap_u), "r"(mb + MB_U), "r"((cta >> 1) * 8), "r"(rank * 1024 + i * 256) : "memory");
        mbar_expect(mb + MB_PEER, 8192);
        #pragma unroll
        for (int i = 0; i < 8; i++) mbar_expect(mb + MB_RX + 8 * i, 1024);
      }
      mbar_wait(mb + MB_U);
      STAMP(2);
      const int chs = (lane & 7) - rank * 4, m = lane >> 3;
      const uint32_t base = ((unsigned)chs < 4u) ? sb + SM_UA + chs * UA_CH + m * UA_ARR + (63 - rank * 32) * 16
                                                 : sb + SM_XS + 64 + (chs & 3) * XS_CH + m * 512 + 31 * 16;
      #pragma unroll
      for (int hh = 0; hh < 2; hh++) {
        uint32_t r[4][4];
        #pragma unroll
        for (int it = 0; it < 4; it++) ldsm4t(sb + SM_RAW + ((bw * 8 + hh * 4 + it) * 32 + lane) * 16, r[it]);
        #pragma unroll
        for (int it = 0; it < 4; it++) stsm4(base - (bw * 8 + hh * 4 + it) * 16, r[it]);
      }
      fence_async();
      asm volatile("barrier.cluster.wait.aligned;" ::: "memory");
      bar_sync(11, 128);
      if (lane < 4) {
        dsmem_copy(mapa(sb + SM_UA + bw * UA_CH + lane * UA_ARR + (32 - rank * 32) * 16, rank ^ 1),
                   sb + SM_XS + 64 + bw * XS_CH + lane * 512, 512, mapa(mb + MB_PEER, rank ^ 1));
      }
      STAMP(3);
      mbar_wait(mb + MB_PEER);
      if (bt == 0) mbar_arrive(mb + MB_URDY);
      STAMP(4);
    } else {
      mbar_wait(mb + MB_ROW);
      {
        const uint4 gw0 = lds128(sb + SM_ROW + 16384 + lane * 16), gw1 = lds128(sb + SM_ROW + 16384 + 512 + lane * 16);
        float s[4];
        #pragma unroll
        for (int r = 0; r < 4; r++) {
          const uint4 x0 = lds128(sb + SM_ROW + (aw * 4 + r) * 1024 + lane * 16), x1 = lds128(sb + SM_ROW + (aw * 4 + r) * 1024 + 512 + lane * 16);
          const uint32_t xv[8] = {x0.x, x0.y, x0.z, x0.w, x1.x, x1.y, x1.z, x1.w}, wv[8] = {gw0.x, gw0.y, gw0.z, gw0.w, gw1.x, gw1.y, gw1.z, gw1.w};
          float a = 0.f, b = 0.f;
          #pragma unroll
          for (int i = 0; i < 8; i++) {
            __nv_bfloat162 pr2 = __hmul2(*(const __nv_bfloat162*)&xv[i], *(const __nv_bfloat162*)&wv[i]);
            const uint32_t pv = *(uint32_t*)&pr2;
            a += bf_lo(pv); b += bf_hi(pv);
          }
          s[r] = a + b;
        }
        float t0 = (lane & 1) ? s[1] : s[0], t1 = (lane & 1) ? s[3] : s[2];
        t0 += __shfl_xor_sync(~0u, (lane & 1) ? s[0] : s[1], 1); t1 += __shfl_xor_sync(~0u, (lane & 1) ? s[2] : s[3], 1);
        float t = (lane & 2) ? t1 : t0;
        t += __shfl_xor_sync(~0u, (lane & 2) ? t0 : t1, 2);
        #pragma unroll
        for (int o = 4; o < 32; o <<= 1) t += __shfl_xor_sync(~0u, t, o);
        if (lane < 4) {
          const float gv = __fdividef(1.f, 1.f + exp_acc(-bf16_round(t)));
          const uint32_t w = (pack_bf2(gv, gv) & 0xffffu) | (tag << 16);
          asm volatile("st.relaxed.gpu.global.u32 [%0], %1;" :: "l"(&g_gate[cta * 16 + aw * 4 + lane]), "r"(w) : "memory");
        }
      }
      STAMP(2);
      asm volatile("barrier.cluster.wait.aligned;" ::: "memory");
      mbar_wait(mb + MB_URDY);
      #pragma unroll 1
      for (int kk = 0; kk < 2; kk++) {
        uint32_t x[4], y[4]; int it = 0; bool ok;
        do {
          ok = true;
          #pragma unroll
          for (int k = 0; k < 4; k++) {
            const uint32_t* gp = &g_gate[64 * (aw + 4 * k + 16 * kk) + lane];
            asm volatile("ld.relaxed.gpu.global.u32 %0, [%1];" : "=r"(x[k]) : "l"(gp) : "memory");
            asm volatile("ld.relaxed.gpu.global.u32 %0, [%1];" : "=r"(y[k]) : "l"(gp + 32) : "memory");
          }
          #pragma unroll
          for (int k = 0; k < 4; k++) ok = ok && (x[k] >> 16) == tag && (y[k] >> 16) == tag;
        } while (!ok && ++it < (1 << 18));
        #pragma unroll
        for (int k = 0; k < 4; k++) {
          uint32_t a = sb + SM_GW + ((aw + 4 * k + 16 * kk) * 40 + lane) * 4;
          sts32(a, __byte_perm(y[k], x[k], 0x5410));
          sts32(a + 5120, pack_bf2(1.f - bf_lo(y[k]), 1.f - bf_lo(x[k])));
          const uint32_t ge = sb + SM_GE + ((aw + 4 * k + 16 * kk) * 32 + (lane >> 4) * 8 + (lane & 7)) * 4 + ((lane >> 3) & 1) * 2;
          sts16(ge, x[k]); sts16(ge + 64, y[k]);
        }
      }
      warp_arrive(mb + MB_GW, lane);
      STAMP(4);
    }
    bar_sync(12, 256);
    if (at == 0) __stcg(&g_epoch[cta], epoch);
    #pragma unroll 1
    for (int c = 0; c < 4; c++) {
      const uint32_t yb = sb + (c < 2 ? SM_Y01 + c * Y_CH : SM_Y23 + (c - 2) * 8 * GSLOT);
      if (c == 0) mbar_wait(mb + MB_G23);
      if (at >= 200) {
        const int i = at - 200;
        sts128(yb + (i < 28 ? i * 16 : Y3_OFF - 512 + (i - 28) * 16), 0, 0, 0, 0);
      }
      if (at >= 6 && at < 200) ytab_chunk(sb + SM_UA + c * UA_CH + 63 * 16, yb, at - 8);
      warp_arrive(mb + MB_Y + 8 * c, lane);
      STAMP(5 + c);
    }
    {
      const int k = 7 - aw;
      const uint32_t tk = sb + SM_T + k * 4096 + lane * 16, t3 = sb + SM_T3 + k * 2048 + lane * 16;
      mbar_wait(mb + MB_LOC + 8 * k);
      STAMP(11);
      #pragma unroll
      for (int i = 0; i < 4; i++) {
        const int hf = (i >> 1) ^ rank ^ 1, o = (i & 1) * 512;
        const uint4 a = lds128(tk + hf * 2048 + o), b = lds128(tk + hf * 2048 + 1024 + o), c = k ? lds128(t3 + hf * 1024 + o) : make_uint4(0, 0, 0, 0);
        const uint32_t s0 = hadd(hadd(a.x, b.x), c.x), s1 = hadd(hadd(a.y, b.y), c.y), s2 = hadd(hadd(a.z, b.z), c.z), s3 = hadd(hadd(a.w, b.w), c.w);
        if (i < 2)
          asm volatile("st.async.weak.shared::cluster.mbarrier::complete_tx::bytes.v4.u32 [%0], {%1,%2,%3,%4}, [%5];"
                       :: "r"(mapa(sb + SM_RX + k * 1024 + lane * 16 + o, rank ^ 1)), "r"(s0), "r"(s1), "r"(s2), "r"(s3), "r"(mapa(mb + MB_RX + 8 * k, rank ^ 1)) : "memory");
        else sts128(t3 + hf * 1024 + o, s0, s1, s2, s3);
      }
      __syncwarp();
      mbar_wait(mb + MB_RX + 8 * k);
      STAMP(12);
      const int m = lane >> 3, j = lane & 7;
      const uint32_t src = (((j >> 2) == rank) ? sb + SM_T3 + k * 2048 + rank * 1024 : sb + SM_RX + k * 1024) + (j & 3) * 256;
      const uint32_t ob = sb + SM_T + k * 4096;
      #pragma unroll
      for (int it = 0; it < 4; it++) {
        const int c16 = 4 * it + m;
        uint32_t r[4];
        ldsm4t(src + ((c16 ^ (rank * 2 + (c16 >> 3)) ^ j) * 16), r);
        stsm4(ob + (it * 32 + lane) * 16, r);
      }
      fence_async();
      __syncwarp();
      if (lane == 0) {
        asm volatile("cp.async.bulk.tensor.2d.global.shared::cta.bulk_group [%0, {%2, %3}], [%1];"
                     :: "l"((uint64_t)&tmap_o), "r"(ob), "r"((cta >> 1) * 8), "r"(k * 256 + rank * 128) : "memory");
        asm volatile("cp.async.bulk.commit_group;" ::: "memory");
        asm volatile("cp.async.bulk.wait_group.read 0;" ::: "memory");
      }
      __syncwarp();
      STAMP(13);
    }
    asm volatile("barrier.cluster.arrive.relaxed.aligned;" ::: "memory");
    asm volatile("barrier.cluster.wait.aligned;" ::: "memory");
    STAMP(14);
    STAMP_DUMP();
  }
}

typedef CUresult (*EncodeFn)(CUtensorMap*, CUtensorMapDataType, cuuint32_t, void*, const cuuint64_t*, const cuuint64_t*,
                             const cuuint32_t*, const cuuint32_t*, CUtensorMapInterleave, CUtensorMapSwizzle,
                             CUtensorMapL2promotion, CUtensorMapFloatOOBfill);
}

extern "C" void kernel_launch(void* const* d_in, const int* in_sizes, int n_in, void* d_out, int out_size) {
  (void)in_sizes; (void)n_in; (void)out_size;
  static EncodeFn enc = nullptr;
  if (!enc) {
    void* fn = nullptr; cudaDriverEntryPointQueryResult qr;
    cudaGetDriverEntryPoint("cuTensorMapEncodeTiled", &fn, cudaEnableDefault, &qr);
    enc = (EncodeFn)fn;
    cudaFuncSetAttribute(ssm_gated_kernel, cudaFuncAttributeMaxDynamicSharedMemorySize, SM_TOTAL + STAMP_EXTRA);
  }
  CUtensorMap tm;
  cuuint64_t gd[2] = {(cuuint64_t)DIM, (cuuint64_t)SEQ}; cuuint64_t gs[1] = {(cuuint64_t)DIM * 2};
  cuuint32_t bd[2] = {8, 256}; cuuint32_t es[2] = {1, 1};
  enc(&tm, CU_TENSOR_MAP_DATA_TYPE_BFLOAT16, 2, d_in[0], gd, gs, bd, es, CU_TENSOR_MAP_INTERLEAVE_NONE,
      CU_TENSOR_MAP_SWIZZLE_NONE, CU_TENSOR_MAP_L2_PROMOTION_L2_128B, CU_TENSOR_MAP_FLOAT_OOB_FILL_NONE);
  CUtensorMap to;
  cuuint32_t bo[2] = {8, 128};
  enc(&to, CU_TENSOR_MAP_DATA_TYPE_BFLOAT16, 2, d_out, gd, gs, bo, es, CU_TENSOR_MAP_INTERLEAVE_NONE,
      CU_TENSOR_MAP_SWIZZLE_NONE, CU_TENSOR_MAP_L2_PROMOTION_NONE, CU_TENSOR_MAP_FLOAT_OOB_FILL_NONE);
  Params P;
  typedef const __nv_bfloat16* bp;
  P.u = (bp)d_in[0];
  const int mi[10] = {1, 2, 5, 6, 10, 11, 12, 13, 3, 4}, vi[4] = {7, 14, 8, 15};
  for (int i = 0; i < 10; i++) P.pm[i] = (bp)d_in[mi[i]];
  for (int i = 0; i < 4; i++) P.pv[i] = (bp)d_in[vi[i]];
  P.gate_w = (bp)d_in[16];
  P.out = (__nv_bfloat16*)d_out;
  ssm_gated_kernel<<<NCTA, NTHR, SM_TOTAL + STAMP_EXTRA, cudaStreamPerThread>>>(tm, to, P);
}
```
